```python
import torch

def _softmax(x, axis=-1):
    return torch.softmax(x, dim=axis)
def _gelu(x):
    return torch.nn.functional.gelu(x, approximate="tanh")
def _silu(x):
    return torch.nn.functional.silu(x)
def _sigmoid(x):
    return torch.sigmoid(x)
def _layernorm(x, axis=-1, eps=1e-5):
    m = x.mean(dim=axis, keepdim=True)
    v = x.var(dim=axis, keepdim=True, unbiased=False)
    return (x - m) / torch.sqrt(v + eps)
def _scatter_add(tgt, idx, src, axis=0):
    return tgt.clone().index_add_(axis, idx, src)
def _segment_sum(src, seg, n):
    out = torch.zeros((n,) + src.shape[1:], dtype=src.dtype)
    return out.index_add_(0, seg, src)
def _pad(x, pw):
    flat = tuple(v for pair in reversed(pw) for v in pair)
    return torch.nn.functional.pad(x, flat)

kernel_name = 'parallel_sum__mha_block__dense_activation_relu__prompt'

def setup_inputs():

    _w = (lambda a: (lambda t: t.to(torch.bfloat16) if t.is_floating_point() else t)(torch.as_tensor(a)))
    def _A_setup():
        B, S, D, H = 1, 2048, 1024, 32
        return {
            "x": _w((lambda *s: torch.randn(*s, dtype=torch.bfloat16) * 0.05)(B, S, D)),
            "wqkv": _w((lambda *s: torch.randn(*s, dtype=torch.bfloat16) * 0.05)(D, 3 * D)),
            "wo": _w((lambda *s: torch.randn(*s, dtype=torch.bfloat16) * 0.05)(D, D)),
        }
    _A_in = _A_setup()

    def _B_setup():
        B, S, D, Dff = 1, 2048, 1024, 3584
        return {
            "x": _w((lambda *s: torch.randn(*s, dtype=torch.bfloat16) * 0.05)(B, S, D)),
            "w1": _w((lambda *s: torch.randn(*s, dtype=torch.bfloat16) * 0.05)(D, Dff)),
            "w2": _w((lambda *s: torch.randn(*s, dtype=torch.bfloat16) * 0.05)(Dff, D)),
        }
    _B_in = _B_setup()

    return {
        "A_x": _A_in["x"],
        "A_wqkv": _A_in["wqkv"],
        "A_wo": _A_in["wo"],
        "B_x": _B_in["x"],
        "B_w1": _B_in["w1"],
        "B_w2": _B_in["w2"],
    }

def reference(A_x, A_wqkv, A_wo, B_x, B_w1, B_w2):
    def _A_ref(x, wqkv, wo):
        B, S, D = x.shape
        H = 32
        Dh = D // H
        qkv = (lambda x, *d: x.permute(*d))((x @ wqkv).reshape(B, S, 3, H, Dh), 2, 0, 3, 1, 4)
        q, k, v = qkv[0], qkv[1], qkv[2]
        scores = torch.einsum("bhqd,bhkd->bhqk", q, k) * (Dh ** -0.5)
        p = _softmax(scores, axis=-1)
        o = torch.einsum("bhqk,bhkd->bhqd", p, v)
        return (lambda x, *d: x.permute(*d))(o, 0, 2, 1, 3).reshape(B, S, D) @ wo

    def _B_ref(x, w1, w2):
        h = torch.einsum("bsd,df->bsf", x, w1)
        zero = torch.zeros_like(h)
        h = torch.maximum(h, zero)
        return torch.einsum("bsf,fd->bsd", h, w2)

    x = A_x
    xn = _layernorm(x, axis=-1)
    return x + _A_ref(xn, A_wqkv, A_wo) + _B_ref(xn, B_w1, B_w2)
```

```cpp
#include <cuda_runtime.h>
#include <cuda_bf16.h>
#include <cuda.h>
#include <stdint.h>

#define GD192 1
#define GD128 1

namespace {

constexpr int kS = 2048, kD = 1024, kDff = 3584;
constexpr int kThreads = 512;
constexpr int kCtas = 128;

constexpr uint32_t kSlot = 40960;
constexpr uint32_t kStageOff = 3 * kSlot;
constexpr uint32_t kKvOff = 4 * kSlot + 8192;
constexpr uint32_t kNKv = 5;
constexpr uint32_t kQOff = kKvOff + kNKv * 8192;
constexpr uint32_t kBarOff = kQOff + 2 * 8192;
constexpr uint32_t kSmemBytes = kBarOff + 256 + 1024;
constexpr uint32_t B_GFULL = 0, B_GEMPTY = 4, B_KVFULL = 8, B_KVEMPTY = 13, B_QFULL = 18, B_QEMPTY = 20, B_GST = 22,
                   B_AST = 24;

__device__ __align__(1024) uint8_t g_xn[16 * 16 * 16384];
__device__ __align__(1024) uint8_t g_q[32 * 2048 * 64];
__device__ __align__(1024) uint8_t g_kv[32 * 32 * 8192];
__device__ __align__(1024) uint8_t g_h[16 * 56 * 16384];
__device__ __align__(1024) uint8_t g_o[16 * 32 * 8192];
constexpr int F_XN = 0, F_KV = 16, F_H = 48, F_O = 96, F_DONE = 160, F_COUNT = 161;
__device__ unsigned g_flags[F_COUNT * 32];

__device__ __forceinline__ uint32_t smem_u32(const void* p) { return (uint32_t)__cvta_generic_to_shared(p); }
__device__ __forceinline__ void wgmma_fence() { asm volatile("wgmma.fence.sync.aligned;\n" ::: "memory"); }
__device__ __forceinline__ void wgmma_commit() { asm volatile("wgmma.commit_group.sync.aligned;\n" ::: "memory"); }
template <int N>
__device__ __forceinline__ void wgmma_wait() { asm volatile("wgmma.wait_group.sync.aligned %0;\n" ::"n"(N) : "memory"); }
template <int N>
__device__ __forceinline__ void fence_regs(float (&r)[N]) {
#pragma unroll
  for (int i = 0; i < N; i++) asm volatile("" : "+f"(r[i])::"memory");
}
template <int N>
__device__ __forceinline__ void fence_regs(uint32_t (&r)[N]) {
#pragma unroll
  for (int i = 0; i < N; i++) asm volatile("" : "+r"(r[i])::"memory");
}
__device__ __forceinline__ uint64_t mk_desc(uint32_t lo, uint32_t hi) { return ((uint64_t)hi << 32) | lo; }
__host__ __device__ constexpr uint32_t desc_hi(uint32_t sbo, uint32_t swz) { return (sbo >> 4) | (swz << 30); }
__device__ __forceinline__ uint32_t desc_lo(uint32_t addr, uint32_t lbo) { return ((addr & 0x3FFFF) >> 4) | ((lbo >> 4) << 16); }

__device__ __forceinline__ void mbar_init(uint32_t bar, uint32_t cnt) {
  asm volatile("mbarrier.init.shared::cta.b64 [%0], %1;\n" ::"r"(bar), "r"(cnt) : "memory");
}
__device__ __forceinline__ void mbar_expect_tx(uint32_t bar, uint32_t bytes) {
  asm volatile("mbarrier.arrive.expect_tx.shared::cta.b64 _, [%0], %1;\n" ::"r"(bar), "r"(bytes) : "memory");
}
__device__ __forceinline__ void mbar_arrive(uint32_t bar) {
  asm volatile("mbarrier.arrive.shared::cta.b64 _, [%0];\n" ::"r"(bar) : "memory");
}
__device__ __forceinline__ void mbar_arrive_cta(uint32_t bar, uint32_t cta, uint32_t cnt) {
  asm volatile(
      "{\n.reg .b32 ra;\nmapa.shared::cluster.u32 ra, %0, %1;\nmbarrier.arrive.shared::cluster.b64 _, [ra], %2;\n}\n" ::"r"(bar),
      "r"(cta), "r"(cnt)
      : "memory");
}
__device__ __forceinline__ void mbar_wait(uint32_t bar, uint32_t parity) {
  asm volatile(
      "{\n.reg .pred p, q;\n.reg .u32 it;\nmov.u32 it, 0;\n"
      "LW_%=:\n"
      "mbarrier.try_wait.parity.shared::cta.b64 p, [%0], %1;\n"
      "@p bra LD_%=;\n"
      "add.u32 it, it, 1;\n"
      "setp.lt.u32 q, it, 0x400000;\n"
      "@q bra LW_%=;\n"
      "trap;\n"
      "LD_%=:\n}\n" ::"r"(bar), "r"(parity) : "memory");
}
__device__ __forceinline__ void mbar_wait_sleepy(uint32_t bar, uint32_t parity) {
  asm volatile(
      "{\n.reg .pred p, q;\n.reg .u32 it;\nmov.u32 it, 0;\n"
      "LW_%=:\n"
      "mbarrier.try_wait.parity.shared::cta.b64 p, [%0], %1, 20000;\n"
      "@p bra LD_%=;\n"
      "add.u32 it, it, 1;\n"
      "setp.lt.u32 q, it, 0x400000;\n"
      "@q bra LW_%=;\n"
      "trap;\n"
      "LD_%=:\n}\n" ::"r"(bar), "r"(parity) : "memory");
}
__device__ __forceinline__ uint32_t mapa(uint32_t addr, uint32_t cta) {
  uint32_t r;
  asm("mapa.shared::cluster.u32 %0, %1, %2;\n" : "=r"(r) : "r"(addr), "r"(cta));
  return r;
}
__device__ __forceinline__ void mbar_arrive_cluster_if(uint32_t addr, bool pred) {
  asm volatile("{\n.reg .pred p;\nsetp.ne.u32 p, %1, 0;\n@p mbarrier.arrive.shared::cluster.b64 _, [%0];\n}\n" ::"r"(addr),
               "r"((uint32_t)pred)
               : "memory");
}
__device__ __forceinline__ void flag_wait(const unsigned* f, unsigned target) {
  uint32_t it = 0;
#pragma unroll 1
  while (true) {
    unsigned v;
    asm volatile("ld.acquire.gpu.global.u32 %0, [%1];\n" : "=r"(v) : "l"(f) : "memory");
    if (v >= target) break;
    if (++it > (1u << 22)) asm volatile("trap;");
  }
  asm volatile("fence.proxy.async.global;\n" ::: "memory");
}
__device__ __forceinline__ void flag_add(unsigned* f, unsigned v) {
  asm volatile("red.relaxed.gpu.global.add.u32 [%0], %1;\n" ::"l"(f), "r"(v) : "memory");
}
__device__ __forceinline__ void bulk_g2s(uint32_t dst, const void* src, uint32_t bytes, uint32_t bar) {
  asm volatile("cp.async.bulk.shared::cluster.global.mbarrier::complete_tx::bytes [%0], [%1], %2, [%3];\n" ::"r"(dst),
               "l"(src), "r"(bytes), "r"(bar)
               : "memory");
}
__device__ __forceinline__ void bulk_g2s_mc(uint32_t dst, const void* src, uint32_t bytes, uint32_t bar) {
  asm volatile(
      "cp.async.bulk.shared::cluster.global.mbarrier::complete_tx::bytes.multicast::cluster [%0], [%1], %2, [%3], %4;\n" ::"r"(dst),
      "l"(src), "r"(bytes), "r"(bar), "h"((uint16_t)3)
      : "memory");
}
__device__ __forceinline__ void bulk_s2g(void* dst, uint32_t src, uint32_t bytes) {
  asm volatile("cp.async.bulk.global.shared::cta.bulk_group [%0], [%1], %2;\n" ::"l"(dst), "r"(src), "r"(bytes) : "memory");
}
__device__ __forceinline__ void bulk_commit() { asm volatile("cp.async.bulk.commit_group;\n" ::: "memory"); }
__device__ __forceinline__ void bulk_wait_read() { asm volatile("cp.async.bulk.wait_group.read 0;\n" ::: "memory"); }
__device__ __forceinline__ void bulk_wait_all() { asm volatile("cp.async.bulk.wait_group 0;\n" ::: "memory"); }
__device__ __forceinline__ void tma_2d(uint32_t dst, const CUtensorMap* m, int c0, int c1, uint32_t bar) {
  asm volatile(
      "cp.async.bulk.tensor.2d.shared::cluster.global.mbarrier::complete_tx::bytes [%0], [%1, {%3, %4}], [%2];\n" ::"r"(dst),
      "l"((uint64_t)m), "r"(bar), "r"(c0), "r"(c1)
      : "memory");
}
__device__ __forceinline__ void tma_3d_mc(uint32_t dst, const CUtensorMap* m, int c0, int c1, int c2, uint32_t bar) {
  asm volatile(
      "cp.async.bulk.tensor.3d.shared::cluster.global.mbarrier::complete_tx::bytes.multicast::cluster [%0], [%1, {%3, %4, %5}], "
      "[%2], %6;\n" ::"r"(dst),
      "l"((uint64_t)m), "r"(bar), "r"(c0), "r"(c1), "r"(c2), "h"((uint16_t)3)
      : "memory");
}
__device__ __forceinline__ void tma_4d_mc(uint32_t dst, const CUtensorMap* m, int c0, int c1, int c2, int c3, uint32_t bar) {
  asm volatile(
      "cp.async.bulk.tensor.4d.shared::cluster.global.mbarrier::complete_tx::bytes.multicast::cluster [%0], [%1, {%3, %4, %5, "
      "%6}], [%2], %7;\n" ::"r"(dst),
      "l"((uint64_t)m), "r"(bar), "r"(c0), "r"(c1), "r"(c2), "r"(c3), "h"((uint16_t)3)
      : "memory");
}
__device__ __forceinline__ void tma_store_2d(const CUtensorMap* m, uint32_t src, int c0, int c1) {
  asm volatile("cp.async.bulk.tensor.2d.global.shared::cta.bulk_group [%0, {%2, %3}], [%1];\n" ::"l"((uint64_t)m), "r"(src),
               "r"(c0), "r"(c1)
               : "memory");
}
__device__ __forceinline__ void prefetch_map(const CUtensorMap* m) {
  asm volatile("prefetch.tensormap [%0];\n" ::"l"((uint64_t)m) : "memory");
}
__device__ __forceinline__ void fence_async_smem() { asm volatile("fence.proxy.async.shared::cta;\n" ::: "memory"); }
__device__ __forceinline__ void stsm4(uint32_t addr, uint32_t a, uint32_t b, uint32_t c, uint32_t d) {
  asm volatile("stmatrix.sync.aligned.m8n8.x4.shared.b16 [%0], {%1, %2, %3, %4};\n" ::"r"(addr), "r"(a), "r"(b), "r"(c), "r"(d)
               : "memory");
}
__device__ __forceinline__ void ldsm4(uint32_t addr, uint32_t& a, uint32_t& b, uint32_t& c, uint32_t& d) {
  asm volatile("ldmatrix.sync.aligned.m8n8.x4.shared.b16 {%0, %1, %2, %3}, [%4];\n"
               : "=r"(a), "=r"(b), "=r"(c), "=r"(d)
               : "r"(addr)
               : "memory");
}
__device__ __forceinline__ float ex2(float x) {
  float y;
  asm("ex2.approx.ftz.f32 %0, %1;" : "=f"(y) : "f"(x));
  return y;
}
__device__ __forceinline__ uint32_t pack_bf16(float lo, float hi) {
  uint32_t r;
  asm("cvt.rn.bf16x2.f32 %0, %1, %2;" : "=r"(r) : "f"(hi), "f"(lo));
  return r;
}
__device__ __forceinline__ uint32_t pack_bf16_relu(float lo, float hi) {
  uint32_t r;
  asm("cvt.rn.relu.bf16x2.f32 %0, %1, %2;" : "=r"(r) : "f"(hi), "f"(lo));
  return r;
}
__device__ __forceinline__ float bf_lo(uint32_t v) { return __uint_as_float(v << 16); }
__device__ __forceinline__ float bf_hi(uint32_t v) { return __uint_as_float(v & 0xffff0000u); }
__device__ __forceinline__ float bf_round(float x) { return __bfloat162float(__float2bfloat16_rn(x)); }
__device__ __forceinline__ void named_sync(int id) { asm volatile("bar.sync %0, 128;\n" ::"r"(id) : "memory"); }
__device__ __forceinline__ void cluster_arrive() { asm volatile("barrier.cluster.arrive.relaxed.aligned;\n" ::: "memory"); }
__device__ __forceinline__ void cluster_wait() { asm volatile("barrier.cluster.wait.acquire.aligned;\n" ::: "memory"); }
#define TM(cond, idx)
#define TACC(acc, stmt) do { stmt; } while (0)
#define TPUT(cond, idx, v)

template <int TB>
__device__ __forceinline__ void wgmma_ss_n192(float (&d)[96], uint64_t da, uint64_t db, int scale_d) {
  asm volatile(
      "{\n.reg .pred p;\nsetp.ne.b32 p, %98, 0;\n"
      "wgmma.mma_async.sync.aligned.m64n192k16.f32.bf16.bf16 {"
      "%0, %1, %2, %3, %4, %5, %6, %7, %8, %9, %10, %11, %12, %13, %14, %15, "
      "%16, %17, %18, %19, %20, %21, %22, %23, %24, %25, %26, %27, %28, %29, %30, %31, "
      "%32, %33, %34, %35, %36, %37, %38, %39, %40, %41, %42, %43, %44, %45, %46, %47, "
      "%48, %49, %50, %51, %52, %53, %54, %55, %56, %57, %58, %59, %60, %61, %62, %63, "
      "%64, %65, %66, %67, %68, %69, %70, %71, %72, %73, %74, %75, %76, %77, %78, %79, "
      "%80, %81, %82, %83, %84, %85, %86, %87, %88, %89, %90, %91, %92, %93, %94, %95}, %96, %97, p, 1, 1, 0, %99;\n}\n"
      : "+f"(d[0]), "+f"(d[1]), "+f"(d[2]), "+f"(d[3]), "+f"(d[4]), "+f"(d[5]), "+f"(d[6]), "+f"(d[7]),
        "+f"(d[8]), "+f"(d[9]), "+f"(d[10]), "+f"(d[11]), "+f"(d[12]), "+f"(d[13]), "+f"(d[14]), "+f"(d[15]),
        "+f"(d[16]), "+f"(d[17]), "+f"(d[18]), "+f"(d[19]), "+f"(d[20]), "+f"(d[21]), "+f"(d[22]), "+f"(d[23]),
        "+f"(d[24]), "+f"(d[25]), "+f"(d[26]), "+f"(d[27]), "+f"(d[28]), "+f"(d[29]), "+f"(d[30]), "+f"(d[31]),
        "+f"(d[32]), "+f"(d[33]), "+f"(d[34]), "+f"(d[35]), "+f"(d[36]), "+f"(d[37]), "+f"(d[38]), "+f"(d[39]),
        "+f"(d[40]), "+f"(d[41]), "+f"(d[42]), "+f"(d[43]), "+f"(d[44]), "+f"(d[45]), "+f"(d[46]), "+f"(d[47]),
        "+f"(d[48]), "+f"(d[49]), "+f"(d[50]), "+f"(d[51]), "+f"(d[52]), "+f"(d[53]), "+f"(d[54]), "+f"(d[55]),
        "+f"(d[56]), "+f"(d[57]), "+f"(d[58]), "+f"(d[59]), "+f"(d[60]), "+f"(d[61]), "+f"(d[62]), "+f"(d[63]),
        "+f"(d[64]), "+f"(d[65]), "+f"(d[66]), "+f"(d[67]), "+f"(d[68]), "+f"(d[69]), "+f"(d[70]), "+f"(d[71]),
        "+f"(d[72]), "+f"(d[73]), "+f"(d[74]), "+f"(d[75]), "+f"(d[76]), "+f"(d[77]), "+f"(d[78]), "+f"(d[79]),
        "+f"(d[80]), "+f"(d[81]), "+f"(d[82]), "+f"(d[83]), "+f"(d[84]), "+f"(d[85]), "+f"(d[86]), "+f"(d[87]),
        "+f"(d[88]), "+f"(d[89]), "+f"(d[90]), "+f"(d[91]), "+f"(d[92]), "+f"(d[93]), "+f"(d[94]), "+f"(d[95])
      : "l"(da), "l"(db), "r"(scale_d), "n"(TB));
}
template <int TB>
__device__ __forceinline__ void wgmma_ss_n128(float (&d)[96], uint64_t da, uint64_t db, int scale_d) {
  asm volatile(
      "{\n.reg .pred p;\nsetp.ne.b32 p, %66, 0;\n"
      "wgmma.mma_async.sync.aligned.m64n128k16.f32.bf16.bf16 {"
      "%0, %1, %2, %3, %4, %5, %6, %7, %8, %9, %10, %11, %12, %13, %14, %15, "
      "%16, %17, %18, %19, %20, %21, %22, %23, %24, %25, %26, %27, %28, %29, %30, %31, "
      "%32, %33, %34, %35, %36, %37, %38, %39, %40, %41, %42, %43, %44, %45, %46, %47, "
      "%48, %49, %50, %51, %52, %53, %54, %55, %56, %57, %58, %59, %60, %61, %62, %63}, %64, %65, p, 1, 1, 0, %67;\n}\n"
      : "+f"(d[0]), "+f"(d[1]), "+f"(d[2]), "+f"(d[3]), "+f"(d[4]), "+f"(d[5]), "+f"(d[6]), "+f"(d[7]),
        "+f"(d[8]), "+f"(d[9]), "+f"(d[10]), "+f"(d[11]), "+f"(d[12]), "+f"(d[13]), "+f"(d[14]), "+f"(d[15]),
        "+f"(d[16]), "+f"(d[17]), "+f"(d[18]), "+f"(d[19]), "+f"(d[20]), "+f"(d[21]), "+f"(d[22]), "+f"(d[23]),
        "+f"(d[24]), "+f"(d[25]), "+f"(d[26]), "+f"(d[27]), "+f"(d[28]), "+f"(d[29]), "+f"(d[30]), "+f"(d[31]),
        "+f"(d[32]), "+f"(d[33]), "+f"(d[34]), "+f"(d[35]), "+f"(d[36]), "+f"(d[37]), "+f"(d[38]), "+f"(d[39]),
        "+f"(d[40]), "+f"(d[41]), "+f"(d[42]), "+f"(d[43]), "+f"(d[44]), "+f"(d[45]), "+f"(d[46]), "+f"(d[47]),
        "+f"(d[48]), "+f"(d[49]), "+f"(d[50]), "+f"(d[51]), "+f"(d[52]), "+f"(d[53]), "+f"(d[54]), "+f"(d[55]),
        "+f"(d[56]), "+f"(d[57]), "+f"(d[58]), "+f"(d[59]), "+f"(d[60]), "+f"(d[61]), "+f"(d[62]), "+f"(d[63])
      : "l"(da), "l"(db), "r"(scale_d), "n"(TB));
}
template <int TB>
__device__ __forceinline__ void wgmma_ss_n64(float (&d)[32], uint64_t da, uint64_t db, int scale_d) {
  asm volatile(
      "{\n.reg .pred p;\nsetp.ne.b32 p, %34, 0;\n"
      "wgmma.mma_async.sync.aligned.m64n64k16.f32.bf16.bf16 {"
      "%0, %1, %2, %3, %4, %5, %6, %7, %8, %9, %10, %11, %12, %13, %14, %15, "
      "%16, %17, %18, %19, %20, %21, %22, %23, %24, %25, %26, %27, %28, %29, %30, %31}, %32, %33, p, 1, 1, 0, %35;\n}\n"
      : "+f"(d[0]), "+f"(d[1]), "+f"(d[2]), "+f"(d[3]), "+f"(d[4]), "+f"(d[5]), "+f"(d[6]), "+f"(d[7]),
        "+f"(d[8]), "+f"(d[9]), "+f"(d[10]), "+f"(d[11]), "+f"(d[12]), "+f"(d[13]), "+f"(d[14]), "+f"(d[15]),
        "+f"(d[16]), "+f"(d[17]), "+f"(d[18]), "+f"(d[19]), "+f"(d[20]), "+f"(d[21]), "+f"(d[22]), "+f"(d[23]),
        "+f"(d[24]), "+f"(d[25]), "+f"(d[26]), "+f"(d[27]), "+f"(d[28]), "+f"(d[29]), "+f"(d[30]), "+f"(d[31])
      : "l"(da), "l"(db), "r"(scale_d), "n"(TB));
}
template <int TB>
__device__ __forceinline__ void wgmma_rs_n32(float (&d)[16], uint32_t a0, uint32_t a1, uint32_t a2, uint32_t a3,
                                             uint64_t db, int scale_d) {
  asm volatile(
      "{\n.reg .pred p;\nsetp.ne.b32 p, %21, 0;\n"
      "wgmma.mma_async.sync.aligned.m64n32k16.f32.bf16.bf16 {"
      "%0, %1, %2, %3, %4, %5, %6, %7, %8, %9, %10, %11, %12, %13, %14, %15}, {%16, %17, %18, %19}, %20, p, 1, 1, %22;\n}\n"
      : "+f"(d[0]), "+f"(d[1]), "+f"(d[2]), "+f"(d[3]), "+f"(d[4]), "+f"(d[5]), "+f"(d[6]), "+f"(d[7]),
        "+f"(d[8]), "+f"(d[9]), "+f"(d[10]), "+f"(d[11]), "+f"(d[12]), "+f"(d[13]), "+f"(d[14]), "+f"(d[15])
      : "r"(a0), "r"(a1), "r"(a2), "r"(a3), "l"(db), "r"(scale_d), "n"(TB));
}

template <int N>
__device__ __forceinline__ void wgmma_gemm(float (&d)[96], uint64_t da, uint64_t db, int sc) {
  if constexpr (N == 192) wgmma_ss_n192<1>(d, da, db, sc);
  else wgmma_ss_n128<1>(d, da, db, sc);
}

template <int N, int NKB, int GD, bool OUTK>
__device__ __forceinline__ void gemm_mainloop(float (&d0)[96], float (&d1)[96], uint32_t sb, uint32_t bars,
                                              uint32_t& phase, uint32_t b_lbo, uint32_t b_hi, uint32_t b_k1, uint32_t b_k2,
                                              uint32_t rel_addr, bool rel_lane, uint32_t& twait) {
#pragma unroll 1
  for (int kb = 0; kb < NKB; kb++) {
    const uint32_t s = kb & 3;
    TACC(twait, mbar_wait(bars + (B_GFULL + s) * 8, phase));
    const uint32_t a_addr = sb + s * kSlot;
    const uint32_t a_lo = desc_lo(a_addr, 16);
    const uint32_t b_lo = desc_lo(a_addr + 16384, b_lbo);
    uint32_t a_hi = desc_hi(1024, 1), a_half = 8192 >> 4, a_k2 = 64 >> 4;
    if (OUTK && ((kb >= 40 && kb < 48) || kb >= 64)) { a_hi = desc_hi(512, 2); a_half = 4096 >> 4; a_k2 = 8192 >> 4; }
    wgmma_fence();
#pragma unroll
    for (int k = 0; k < 4; k++) {
      const uint64_t db = mk_desc(b_lo + (k >> 1) * b_k2 + (k & 1) * b_k1, b_hi);
      const uint32_t ak = a_lo + (k >> 1) * a_k2 + (k & 1) * 2;
      const int sc = (k > 0) ? 1 : (kb > 0);
      wgmma_gemm<N>(d0, mk_desc(ak, a_hi), db, sc);
      wgmma_commit();
      wgmma_wait<GD>();
      if (2 * k + 1 == GD) mbar_arrive_cluster_if(rel_addr + ((s + 3) & 3) * 8, rel_lane && kb > 0);
      wgmma_gemm<N>(d1, mk_desc(ak + a_half, a_hi), db, sc);
      wgmma_commit();
      wgmma_wait<GD>();
      if (2 * k + 2 == GD) mbar_arrive_cluster_if(rel_addr + ((s + 3) & 3) * 8, rel_lane && kb > 0);
    }
    if (s == 3) phase ^= 1;
  }
  wgmma_wait<0>();
#pragma unroll
  for (int i = 0; i < N / 2; i++) { asm volatile("" : "+f"(d0[i])::"memory"); asm volatile("" : "+f"(d1[i])::"memory"); }
}

__device__ __forceinline__ void epi_publish(uint32_t bar, int lane) {
  fence_async_smem();
  __syncwarp();
  if (lane == 0) mbar_arrive(bar);
}
__device__ __forceinline__ void epi_qkv(const float (&d)[96], uint32_t base, uint32_t sw, uint32_t scol) {
  const float qs = 0.17677669529663687f * 1.4426950408889634f;
#pragma unroll
  for (int jj = 0; jj < 12; jj++) {
    const float f = jj < 4 ? qs : 1.f;
    stsm4(base + (jj >> 1) * 8192 + ((((jj & 1) * 2 + scol) ^ sw) << 4), pack_bf16(d[8 * jj] * f, d[8 * jj + 1] * f),
          pack_bf16(d[8 * jj + 2] * f, d[8 * jj + 3] * f), pack_bf16(d[8 * jj + 4] * f, d[8 * jj + 5] * f),
          pack_bf16(d[8 * jj + 6] * f, d[8 * jj + 7] * f));
  }
}
template <int NR>
__device__ __forceinline__ void epi_relu(const float (&d)[96], uint32_t base, uint32_t sw, uint32_t scol) {
#pragma unroll
  for (int jj = 0; jj < NR / 8; jj++)
    stsm4(base + (jj >> 2) * 16384 + ((((jj & 3) * 2 + scol) ^ sw) << 4), pack_bf16_relu(d[8 * jj], d[8 * jj + 1]),
          pack_bf16_relu(d[8 * jj + 2], d[8 * jj + 3]), pack_bf16_relu(d[8 * jj + 4], d[8 * jj + 5]),
          pack_bf16_relu(d[8 * jj + 6], d[8 * jj + 7]));
}
__device__ __forceinline__ void epi_out(const float (&d)[96], uint32_t base, uint32_t sw, uint32_t scol) {
#pragma unroll
  for (int jj = 0; jj < 8; jj++) {
    const uint32_t a = base + (jj >> 2) * 16384 + ((((jj & 3) * 2 + scol) ^ sw) << 4);
    uint32_t x0, x1, x2, x3;
    ldsm4(a, x0, x1, x2, x3);
    stsm4(a, pack_bf16(d[8 * jj] + bf_lo(x0), d[8 * jj + 1] + bf_hi(x0)), pack_bf16(d[8 * jj + 2] + bf_lo(x1), d[8 * jj + 3] + bf_hi(x1)),
          pack_bf16(d[8 * jj + 4] + bf_lo(x2), d[8 * jj + 5] + bf_hi(x2)), pack_bf16(d[8 * jj + 6] + bf_lo(x3), d[8 * jj + 7] + bf_hi(x3)));
  }
}

__device__ __noinline__ void attn_exact(float* o_out, uint32_t q_smem_row_addr, const uint8_t* kv_head) {
  const int lane = threadIdx.x & 31, g = lane >> 2, t = lane & 3;
  uint32_t qa[2][4];
  {
    const int r = (lane & 7) + ((lane >> 3) & 1) * 8;
#pragma unroll
    for (int k = 0; k < 2; k++) {
      const int c16 = 2 * k + (lane >> 4);
      ldsm4(q_smem_row_addr + r * 64 + ((c16 ^ ((r >> 1) & 3)) << 4), qa[k][0], qa[k][1], qa[k][2], qa[k][3]);
    }
  }
  float o[16];
#pragma unroll
  for (int i = 0; i < 16; i++) o[i] = 0.f;
  float m0 = -INFINITY, m1 = -INFINITY, l0 = 0.f, l1 = 0.f;
#pragma unroll 1
  for (int kc = 0; kc < kS / 16; kc++) {
    const uint8_t* kt = kv_head + (kc >> 2) * 8192;
    const int k0 = (kc & 3) * 16;
    float s[2][4];
#pragma unroll
    for (int nb = 0; nb < 2; nb++) {
      s[nb][0] = s[nb][1] = s[nb][2] = s[nb][3] = 0.f;
      const int key = k0 + nb * 8 + g;
#pragma unroll
      for (int k = 0; k < 2; k++) {
        const uint32_t b0 = __ldcg((const uint32_t*)(kt + key * 64 + (((2 * k) ^ ((key >> 1) & 3)) << 4) + t * 4));
        const uint32_t b1 = __ldcg((const uint32_t*)(kt + key * 64 + (((2 * k + 1) ^ ((key >> 1) & 3)) << 4) + t * 4));
        asm volatile(
            "mma.sync.aligned.m16n8k16.row.col.f32.bf16.bf16.f32 {%0,%1,%2,%3}, {%4,%5,%6,%7}, {%8,%9}, {%0,%1,%2,%3};\n"
            : "+f"(s[nb][0]), "+f"(s[nb][1]), "+f"(s[nb][2]), "+f"(s[nb][3])
            : "r"(qa[k][0]), "r"(qa[k][1]), "r"(qa[k][2]), "r"(qa[k][3]), "r"(b0), "r"(b1));
      }
    }
    float x0 = fmaxf(fmaxf(s[0][0], s[0][1]), fmaxf(s[1][0], s[1][1]));
    float x1 = fmaxf(fmaxf(s[0][2], s[0][3]), fmaxf(s[1][2], s[1][3]));
    x0 = fmaxf(x0, __shfl_xor_sync(~0u, x0, 1)); x1 = fmaxf(x1, __shfl_xor_sync(~0u, x1, 1));
    x0 = fmaxf(x0, __shfl_xor_sync(~0u, x0, 2)); x1 = fmaxf(x1, __shfl_xor_sync(~0u, x1, 2));
    x0 = fmaxf(x0, m0); x1 = fmaxf(x1, m1);
    const float c0 = ex2(m0 - x0), c1 = ex2(m1 - x1);
    m0 = x0; m1 = x1;
    uint32_t p[4];
    {
      const float e00 = ex2(s[0][0] - m0), e01 = ex2(s[0][1] - m0), e02 = ex2(s[0][2] - m1), e03 = ex2(s[0][3] - m1);
      const float e10 = ex2(s[1][0] - m0), e11 = ex2(s[1][1] - m0), e12 = ex2(s[1][2] - m1), e13 = ex2(s[1][3] - m1);
      l0 = l0 * c0 + (e00 + e01 + e10 + e11);
      l1 = l1 * c1 + (e02 + e03 + e12 + e13);
      p[0] = pack_bf16(e00, e01); p[1] = pack_bf16(e02, e03); p[2] = pack_bf16(e10, e11); p[3] = pack_bf16(e12, e13);
    }
    const uint8_t* vt = kt + 4096;
#pragma unroll
    for (int nb = 0; nb < 4; nb++) {
      uint32_t hv[4];
#pragma unroll
      for (int i = 0; i < 4; i++) {
        const int key = k0 + 2 * t + (i & 1) + (i >> 1) * 8;
        hv[i] = __ldcg((const unsigned short*)(vt + key * 64 + ((nb ^ ((key >> 1) & 3)) << 4) + g * 2));
      }
      const uint32_t b0 = hv[0] | (hv[1] << 16), b1 = hv[2] | (hv[3] << 16);
      o[4 * nb] *= c0; o[4 * nb + 1] *= c0; o[4 * nb + 2] *= c1; o[4 * nb + 3] *= c1;
      asm volatile(
          "mma.sync.aligned.m16n8k16.row.col.f32.bf16.bf16.f32 {%0,%1,%2,%3}, {%4,%5,%6,%7}, {%8,%9}, {%0,%1,%2,%3};\n"
          : "+f"(o[4 * nb]), "+f"(o[4 * nb + 1]), "+f"(o[4 * nb + 2]), "+f"(o[4 * nb + 3])
          : "r"(p[0]), "r"(p[1]), "r"(p[2]), "r"(p[3]), "r"(b0), "r"(b1));
    }
  }
  l0 += __shfl_xor_sync(~0u, l0, 1); l1 += __shfl_xor_sync(~0u, l1, 1);
  l0 += __shfl_xor_sync(~0u, l0, 2); l1 += __shfl_xor_sync(~0u, l1, 2);
  const float i0 = 1.f / l0, i1 = 1.f / l1;
#pragma unroll
  for (int nb = 0; nb < 4; nb++) {
    o_out[4 * nb] = o[4 * nb] * i0; o_out[4 * nb + 1] = o[4 * nb + 1] * i0;
    o_out[4 * nb + 2] = o[4 * nb + 2] * i1; o_out[4 * nb + 3] = o[4 * nb + 3] * i1;
  }
}

struct Params {
  CUtensorMap wqkv, w1a, w1b, w2, wo, x, out;
  const __nv_bfloat16* xptr;
};

__global__ void __cluster_dims__(2, 1, 1) __launch_bounds__(kThreads, 1) fused_block_kernel(const __grid_constant__ Params P) {
  extern __shared__ __align__(1024) uint8_t smem_raw[];
  const uint32_t sb = (smem_u32(smem_raw) + 1023) & ~1023u;
  const uint32_t bars = sb + kBarOff;
  const int warp = __shfl_sync(~0u, threadIdx.x >> 5, 0);
  const int lane = threadIdx.x & 31;
  const uint32_t rank = blockIdx.x & 1;
  const int cl = blockIdx.x >> 1;
  const int c = cl & 7;
  const int m = (cl >> 3) * 2 + rank;
  TM(threadIdx.x == 0, 0);

  if (threadIdx.x == 0) {
    for (int i = 0; i < 4; i++) { mbar_init(bars + (B_GFULL + i) * 8, 1); mbar_init(bars + (B_GEMPTY + i) * 8, 8); }
    for (int i = 0; i < (int)kNKv; i++) { mbar_init(bars + (B_KVFULL + i) * 8, 1); mbar_init(bars + (B_KVEMPTY + i) * 8, 16); }
    for (int i = 0; i < 2; i++) { mbar_init(bars + (B_QFULL + i) * 8, 1); mbar_init(bars + (B_QEMPTY + i) * 8, 1); mbar_init(bars + (B_GST + i) * 8, 4); }
    for (int i = 0; i < 4; i++) mbar_init(bars + (B_AST + i) * 8, 4);
    asm volatile("fence.mbarrier_init.release.cluster;\n" ::: "memory");
  }
  __syncthreads();
  cluster_arrive();

  if (warp < 4) {
    asm volatile("setmaxnreg.dec.sync.aligned.u32 40;\n");
    if (warp == 0 && lane == 0) { prefetch_map(&P.wqkv); prefetch_map(&P.w1a); prefetch_map(&P.w1b); prefetch_map(&P.w2); prefetch_map(&P.wo); prefetch_map(&P.x); }
    if (warp == 2 && lane == 0) prefetch_map(&P.out);
    cluster_wait();
    if (lane == 0) {
      if (warp == 0) {
        uint32_t ph = 1;
        const uint8_t* xn = g_xn + (size_t)m * 16 * 16384;
        for (int s = 0; s < 4; s++) {
          mbar_expect_tx(bars + (B_GFULL + s) * 8, 16384 + 24576);
          tma_4d_mc(sb + s * kSlot + 16384 + rank * 12288, &P.wqkv, 32 * c, s * 64 + rank * 32, 0, 0, bars + (B_GFULL + s) * 8);
        }
        flag_wait(&g_flags[(F_XN + m) * 32], 64);
        TM(true, 1);
        for (int s = 0; s < 4; s++) bulk_g2s(sb + s * kSlot, xn + s * 16384, 16384, bars + (B_GFULL + s) * 8);
        ph ^= 1;
#pragma unroll 1
        for (int i = 4; i < 80; i++) {
          const int t = i >> 4, kb = i & 15;
          const uint32_t s = i & 3, full = bars + (B_GFULL + s) * 8, dst = sb + s * kSlot;
          mbar_wait_sleepy(bars + (B_GEMPTY + s) * 8, ph);
          mbar_expect_tx(full, t < 3 ? 16384 + 24576 : 16384 + 16384);
          const int krow = kb * 64 + rank * 32;
          if (t < 2) tma_4d_mc(dst + 16384 + rank * 12288, &P.wqkv, 32 * c, krow, 2 * t, 0, full);
          else if (t == 2) tma_3d_mc(dst + 16384 + rank * 12288, &P.w1a, 0, krow, 7 * c, full);
          else tma_3d_mc(dst + 16384 + rank * 8192, &P.w1b, 0, krow, 7 * c + 2 * t - 3, full);
          bulk_g2s(dst, xn + kb * 16384, 16384, full);
          if (s == 3) ph ^= 1;
        }
#pragma unroll 1
        for (int i = 0; i < 72; i++) {
          const uint32_t s = i & 3, full = bars + (B_GFULL + s) * 8, dst = sb + s * kSlot;
          mbar_wait_sleepy(bars + (B_GEMPTY + s) * 8, ph);
          mbar_expect_tx(full, 32768);
          const bool is_o = (i >= 40 && i < 48) || i >= 64;
          if (is_o) {
            const int j = i < 48 ? i - 40 : i - 56;
            tma_3d_mc(dst + 16384 + rank * 8192, &P.wo, 0, j * 64 + rank * 32, 2 * c, full);
            if ((j & 3) == 0) flag_wait(&g_flags[(F_O + m * 4 + (j >> 2)) * 32], 16);
            bulk_g2s(dst, g_o + ((size_t)m * 32 + 2 * j) * 8192, 16384, full);
          } else {
            int hk;
            if (i < 24) hk = (i / 3) * 7 + (i % 3);
            else if (i < 40) hk = ((i - 24) >> 1) * 7 + 3 + (i & 1);
            else hk = ((i - 48) >> 1) * 7 + 5 + (i & 1);
            tma_3d_mc(dst + 16384 + rank * 8192, &P.w2, 0, hk * 64 + rank * 32, 2 * c, full);
            if (i == 0) flag_wait(&g_flags[(F_H + m * 3 + 0) * 32], 16);
            if (i == 24) flag_wait(&g_flags[(F_H + m * 3 + 1) * 32], 16);
            if (i == 48) flag_wait(&g_flags[(F_H + m * 3 + 2) * 32], 16);
            bulk_g2s(dst, g_h + ((size_t)m * 56 + hk) * 16384, 16384, full);
          }
          if (s == 3) ph ^= 1;
        }
        mbar_wait_sleepy(bars + (B_GEMPTY + 0) * 8, ph);
        mbar_expect_tx(bars + (B_GFULL + 0) * 8, 32768);
        tma_2d(sb, &P.x, 128 * c, 128 * m, bars + (B_GFULL + 0) * 8);
        tma_2d(sb + 16384, &P.x, 128 * c + 64, 128 * m, bars + (B_GFULL + 0) * 8);
      } else if (warp == 1) {
        uint32_t s = 0, ph = 1;
#pragma unroll 1
        for (int g = 0; g <= 128; g++) {
          if ((g & 31) == 0 && g < 128) {
            const int u = g >> 5, head = 8 * u + c;
            flag_wait(&g_flags[(F_KV + head) * 32], 32);
            TM(true, 2 + u);
            if (u >= 2) mbar_wait_sleepy(bars + (B_QEMPTY + (u & 1)) * 8, 0);
            mbar_expect_tx(bars + (B_QFULL + (u & 1)) * 8, 8192);
            bulk_g2s(sb + kQOff + (u & 1) * 8192, g_q + ((size_t)head * kS + m * 128) * 64, 8192, bars + (B_QFULL + (u & 1)) * 8);
          }
          const int t = rank ? max(g - 1, 0) : min(g, 127);
          const uint8_t* src = g_kv + (size_t)((8 * (t >> 5) + c) * 32 + (t & 31)) * 8192 + rank * 4096;
          mbar_wait_sleepy(bars + (B_KVEMPTY + s) * 8, ph);
          mbar_expect_tx(bars + (B_KVFULL + s) * 8, 8192);
          bulk_g2s_mc(sb + kKvOff + s * 8192 + rank * 4096, src, 4096, bars + (B_KVFULL + s) * 8);
          if (++s == kNKv) { s = 0; ph ^= 1; }
        }
      } else if (warp == 2) {
        const uint32_t st = sb + kStageOff;
#pragma unroll 1
        for (int t = 0; t < 5; t++) {
#pragma unroll 1
          for (int h = 0; h < 2; h++) {
            mbar_wait_sleepy(bars + (B_GST + h) * 8, t & 1);
            if (t < 2) {
              for (int r = 0; r < 2; r++) {
                const int head = 8 * (2 * t + r) + c;
                bulk_s2g(g_q + ((size_t)head * kS + m * 128 + h * 64) * 64, st + r * 8192 + h * 4096, 4096);
                uint8_t* kv = g_kv + ((size_t)head * 32 + 2 * m + h) * 8192;
                bulk_s2g(kv, st + (2 + r) * 8192 + h * 4096, 4096);
                bulk_s2g(kv + 4096, st + (4 + r) * 8192 + h * 4096, 4096);
              }
            } else {
              const int a0 = t == 2 ? 7 * c : 7 * c + 2 * t - 3, na = t == 2 ? 3 : 2;
              for (int a = 0; a < na; a++)
                bulk_s2g(g_h + ((size_t)m * 56 + a0 + a) * 16384 + h * 8192, st + a * 16384 + h * 8192, 8192);
            }
            bulk_commit();
          }
          bulk_wait_read();
          TM(t < 2, 52 + 2 * t);
          mbar_arrive_cta(bars + (B_GEMPTY + 3) * 8, 0, 4);
          mbar_arrive_cta(bars + (B_GEMPTY + 3) * 8, 1, 4);
          bulk_wait_all();
          TM(t < 2, 53 + 2 * t);
          if (t < 2) {
            flag_add(&g_flags[(F_KV + 16 * t + c) * 32], 2);
            flag_add(&g_flags[(F_KV + 16 * t + 8 + c) * 32], 2);
          } else {
            flag_add(&g_flags[(F_H + m * 3 + t - 2) * 32], 2);
          }
          TM(true, 8 + t);
        }
#pragma unroll 1
        for (int h = 0; h < 2; h++) {
          mbar_wait_sleepy(bars + (B_GST + h) * 8, 1);
          tma_store_2d(&P.out, sb + h * 8192, 128 * c, 128 * m + 64 * h);
          tma_store_2d(&P.out, sb + 16384 + h * 8192, 128 * c + 64, 128 * m + 64 * h);
          bulk_commit();
        }
        bulk_wait_all();
        TM(true, 13);
      } else {
#pragma unroll 1
        for (int u = 0; u < 4; u++) {
          for (int w = 0; w < 2; w++) {
            mbar_wait_sleepy(bars + (B_AST + w * 2 + (u & 1)) * 8, u >> 1);
            bulk_s2g(g_o + ((size_t)m * 32 + 8 * u + c) * 8192 + w * 4096, sb + kQOff + (u & 1) * 8192 + w * 4096, 4096);
            bulk_commit();
          }
          bulk_wait_read();
          mbar_arrive(bars + (B_QEMPTY + (u & 1)) * 8);
          bulk_wait_all();
          flag_add(&g_flags[(F_O + m * 4 + u) * 32], 2);
          TM(true, 14 + u);
        }
      }
    }
    __syncwarp();
  } else if (warp < 8) {
    asm volatile("setmaxnreg.inc.sync.aligned.u32 240;\n");
    cluster_wait();
    const int w = warp & 3;
    const bool rel_lane = lane < 2;
    const uint32_t rel_addr = mapa(bars + B_GEMPTY * 8, lane & 1);
    uint32_t phase = 0, twait = 0;
    const uint32_t srow = w * 16 + (lane & 7) + ((lane >> 3) & 1) * 8, scol = lane >> 4;
    const uint32_t st = sb + kStageOff;
    const uint32_t gst0 = bars + B_GST * 8, gst1 = gst0 + 8;
    {
      float d0[96], d1[96];
#pragma unroll
      for (int i = 0; i < 96; i++) { d0[i] = 0.f; d1[i] = 0.f; }
#pragma unroll 1
      for (int t = 0; t < 3; t++) {
        gemm_mainloop<192, 16, GD192, false>(d0, d1, sb, bars, phase, t < 2 ? 2048 : 4096, t < 2 ? desc_hi(512, 2) : desc_hi(1024, 1),
                                             t < 2 ? 1024 >> 4 : 2048 >> 4, 12288 >> 4, rel_addr, rel_lane, twait);
        TM(threadIdx.x == 128, 20 + t); TPUT(threadIdx.x == 128, 41 + t, twait);
        named_sync(1);
        if (t < 2) {
          epi_qkv(d0, st + srow * 64, (srow >> 1) & 3, scol);
          epi_publish(gst0, lane);
          epi_qkv(d1, st + srow * 64 + 4096, (srow >> 1) & 3, scol);
          epi_publish(gst1, lane);
          TM(threadIdx.x == 128, 26 + t);
        } else {
          epi_relu<96>(d0, st + srow * 128, srow & 7, scol);
          epi_publish(gst0, lane);
          epi_relu<96>(d1, st + srow * 128 + 8192, srow & 7, scol);
          epi_publish(gst1, lane);
        }
      }
#pragma unroll 1
      for (int t = 3; t < 5; t++) {
        gemm_mainloop<128, 16, GD128, false>(d0, d1, sb, bars, phase, 4096, desc_hi(1024, 1), 2048 >> 4, 8192 >> 4, rel_addr, rel_lane, twait);
        TM(threadIdx.x == 128, 20 + t); TPUT(threadIdx.x == 128, 41 + t, twait);
        named_sync(1);
        epi_relu<64>(d0, st + srow * 128, srow & 7, scol);
        epi_publish(gst0, lane);
        epi_relu<64>(d1, st + srow * 128 + 8192, srow & 7, scol);
        epi_publish(gst1, lane);
      }
      gemm_mainloop<128, 72, GD128, true>(d0, d1, sb, bars, phase, 4096, desc_hi(1024, 1), 2048 >> 4, 8192 >> 4, rel_addr, rel_lane, twait);
      TM(threadIdx.x == 128, 25); TPUT(threadIdx.x == 128, 51, twait);
      mbar_wait(bars + (B_GFULL + 0) * 8, phase);
      epi_out(d0, sb + srow * 128, srow & 7, scol);
      epi_publish(gst0, lane);
      epi_out(d1, sb + srow * 128 + 8192, srow & 7, scol);
      epi_publish(gst1, lane);
    }
  } else {
    asm volatile("setmaxnreg.dec.sync.aligned.u32 112;\n");
    {
      const int r0 = c * 16 + (warp - 8) * 2;
      const uint32_t lnbuf = sb + kKvOff + (warp - 8) * 4096;
      uint4 v[2][4];
#pragma unroll
      for (int i = 0; i < 2; i++)
#pragma unroll
        for (int j = 0; j < 4; j++)
          v[i][j] = __ldg(reinterpret_cast<const uint4*>(P.xptr + (size_t)(m * 128 + r0 + i) * kD) + lane + 32 * j);
      TM(threadIdx.x == 256, 56);
#pragma unroll
      for (int i = 0; i < 2; i++) {
        float f[32];
#pragma unroll
        for (int j = 0; j < 4; j++) {
          f[8 * j] = bf_lo(v[i][j].x); f[8 * j + 1] = bf_hi(v[i][j].x); f[8 * j + 2] = bf_lo(v[i][j].y); f[8 * j + 3] = bf_hi(v[i][j].y);
          f[8 * j + 4] = bf_lo(v[i][j].z); f[8 * j + 5] = bf_hi(v[i][j].z); f[8 * j + 6] = bf_lo(v[i][j].w); f[8 * j + 7] = bf_hi(v[i][j].w);
        }
        float sum = 0.f;
#pragma unroll
        for (int j = 0; j < 32; j++) sum += f[j];
#pragma unroll
        for (int o = 16; o; o >>= 1) sum += __shfl_xor_sync(~0u, sum, o);
        const float mean = sum * (1.f / kD);
        TM(threadIdx.x == 256 && i == 0 && mean != 123.f, 57);
        float sq = 0.f;
#pragma unroll
        for (int j = 0; j < 32; j++) { const float dlt = f[j] - mean; sq = fmaf(dlt, dlt, sq); }
#pragma unroll
        for (int o = 16; o; o >>= 1) sq += __shfl_xor_sync(~0u, sq, o);
        const float mb = bf_round(mean);
        const float den = bf_round(sqrtf(bf_round(bf_round(sq * (1.f / kD)) + 1e-5f)));
        const float inv = 1.f / den;
        const int r = r0 + i;
#pragma unroll
        for (int j = 0; j < 4; j++) {
          uint4 o;
          o.x = pack_bf16(bf_round(f[8 * j] - mb) * inv, bf_round(f[8 * j + 1] - mb) * inv);
          o.y = pack_bf16(bf_round(f[8 * j + 2] - mb) * inv, bf_round(f[8 * j + 3] - mb) * inv);
          o.z = pack_bf16(bf_round(f[8 * j + 4] - mb) * inv, bf_round(f[8 * j + 5] - mb) * inv);
          o.w = pack_bf16(bf_round(f[8 * j + 6] - mb) * inv, bf_round(f[8 * j + 7] - mb) * inv);
          const int ch = lane + 32 * j;
          asm volatile("st.shared.v4.b32 [%0], {%1, %2, %3, %4};\n" ::"r"(lnbuf + (ch >> 3) * 256 + i * 128 + (((ch & 7) ^ (r & 7)) << 4)),
                       "r"(o.x), "r"(o.y), "r"(o.z), "r"(o.w)
                       : "memory");
        }
      }
      TM(threadIdx.x == 256, 58);
      fence_async_smem();
      __syncwarp();
      if (lane < 16) {
        bulk_s2g(g_xn + ((size_t)(m * 16 + lane) * 128 + r0) * 128, lnbuf + lane * 256, 256);
        bulk_commit();
        bulk_wait_all();
      }
      __syncwarp();
      if (lane == 0) flag_add(&g_flags[(F_XN + m) * 32], 1);
      TM(threadIdx.x == 256, 59);
    }
    cluster_wait();
    const int aw = (warp - 8) >> 2, w = warp & 3;
    const bool rel_lane = lane < 2;
    const uint32_t rel_addr = mapa(bars + B_KVEMPTY * 8, lane & 1);
    float s[32], o[16];
    uint32_t p[16];
#pragma unroll
    for (int i = 0; i < 16; i++) { o[i] = 0.f; p[i] = 0u; }
#pragma unroll
    for (int i = 0; i < 32; i++) s[i] = 0.f;
    float l0 = 0.f, l1 = 0.f;
    const uint32_t hi64 = desc_hi(512, 2);
    const uint32_t kv_lo0 = desc_lo(sb + kKvOff, 16);
    uint32_t st = 0, ph = 0;
    uint32_t rel_cur = rel_addr;
    auto issue_pv = [&](int acc) {
      const uint32_t v_lo = kv_lo0 + st * 512 + 256;
      wgmma_rs_n32<1>(o, p[0], p[1], p[2], p[3], mk_desc(v_lo, hi64), acc);
      wgmma_rs_n32<1>(o, p[4], p[5], p[6], p[7], mk_desc(v_lo + 64, hi64), 1);
      wgmma_rs_n32<1>(o, p[8], p[9], p[10], p[11], mk_desc(v_lo + 128, hi64), 1);
      wgmma_rs_n32<1>(o, p[12], p[13], p[14], p[15], mk_desc(v_lo + 192, hi64), 1);
    };
    auto issue_qk = [&](uint32_t q_lo) {
      const uint32_t k_lo = kv_lo0 + st * 512;
      wgmma_ss_n64<0>(s, mk_desc(q_lo, hi64), mk_desc(k_lo, hi64), 0);
      wgmma_ss_n64<0>(s, mk_desc(q_lo + 2, hi64), mk_desc(k_lo + 2, hi64), 1);
    };
    auto softmax_tile = [&]() {
#pragma unroll
      for (int i = 0; i < 8; i++) {
        const float e0 = ex2(s[4 * i]), e1 = ex2(s[4 * i + 1]), e2 = ex2(s[4 * i + 2]), e3 = ex2(s[4 * i + 3]);
        l0 += e0 + e1; l1 += e2 + e3;
        p[2 * i] = pack_bf16(e0, e1); p[2 * i + 1] = pack_bf16(e2, e3);
      }
    };
    auto advance = [&]() {
      mbar_arrive_cluster_if(rel_cur, rel_lane);
      rel_cur += 8;
      if (++st == kNKv) { st = 0; ph ^= 1; rel_cur = rel_addr; }
    };
#pragma unroll 1
    for (int u = 0; u <= 4; u++) {
      const uint32_t q_lo = desc_lo(sb + kQOff + (u & 1) * 8192 + aw * 4096, 16);
      if (u < 4) mbar_wait(bars + (B_QFULL + (u & 1)) * 8, u >> 1);
      mbar_wait(bars + (B_KVFULL + st) * 8, ph);
      fence_regs(s); fence_regs(o); fence_regs(p);
      wgmma_fence();
      issue_pv(1);
      issue_qk(q_lo);
      wgmma_commit();
      wgmma_wait<0>();
      fence_regs(s); fence_regs(o); fence_regs(p);
      advance();
      if (u > 0) {
        const uint32_t ob = sb + kQOff + ((u - 1) & 1) * 8192 + aw * 4096;
        l0 += __shfl_xor_sync(~0u, l0, 1); l1 += __shfl_xor_sync(~0u, l1, 1);
        l0 += __shfl_xor_sync(~0u, l0, 2); l1 += __shfl_xor_sync(~0u, l1, 2);
        bool ok = l0 >= 8.271806e-25f && l0 <= 1.2676506e30f && l1 >= 8.271806e-25f && l1 <= 1.2676506e30f;
#pragma unroll
        for (int i = 0; i < 16; i++) ok = ok && (fabsf(o[i]) <= 3.0e38f);
        const float i0 = 1.f / l0, i1 = 1.f / l1;
        uint32_t r[8];
#pragma unroll
        for (int i = 0; i < 4; i++) {
          r[2 * i] = pack_bf16(o[4 * i] * i0, o[4 * i + 1] * i0);
          r[2 * i + 1] = pack_bf16(o[4 * i + 2] * i1, o[4 * i + 3] * i1);
        }
        if (__any_sync(~0u, !ok)) {
          float e[16];
          attn_exact(e, ob + w * 1024, g_kv + (size_t)(8 * (u - 1) + c) * 32 * 8192);
#pragma unroll
          for (int i = 0; i < 8; i++) r[i] = pack_bf16(e[2 * i], e[2 * i + 1]);
        }
        __syncwarp();
        const uint32_t srow = w * 16 + (lane & 7) + ((lane >> 3) & 1) * 8, scol = lane >> 4;
        const uint32_t base = ob + srow * 64, sw = (srow >> 1) & 3;
        stsm4(base + ((scol ^ sw) << 4), r[0], r[1], r[2], r[3]);
        stsm4(base + (((2 + scol) ^ sw) << 4), r[4], r[5], r[6], r[7]);
        epi_publish(bars + (B_AST + aw * 2 + ((u - 1) & 1)) * 8, lane);
        l0 = 0.f; l1 = 0.f;
        TM(threadIdx.x == 256, 30 + u);
        TPUT(threadIdx.x == 256, 46 + u, clk32());
      }
      if (u == 4) break;
      softmax_tile();
#pragma unroll 1
      for (int j = 1; j < 32; j++) {
        mbar_wait(bars + (B_KVFULL + st) * 8, ph);
        fence_regs(s); fence_regs(o); fence_regs(p);
        wgmma_fence(); issue_pv(j != 1); issue_qk(q_lo); wgmma_commit(); wgmma_wait<0>();
        fence_regs(s); fence_regs(o); fence_regs(p);
        advance();
        softmax_tile();
      }
    }
  }

  cluster_arrive();
  cluster_wait();
  if (threadIdx.x == 0) {
    TM(true, 40);
    asm volatile("fence.acq_rel.gpu;\n" ::: "memory");
    const unsigned old = atomicAdd(&g_flags[F_DONE * 32], 1u);
    if (old == kCtas - 1) {
      asm volatile("fence.acq_rel.gpu;\n" ::: "memory");
      for (int i = 0; i < F_COUNT; i++) g_flags[i * 32] = 0u;
    }
  }
}

typedef CUresult (*EncodeFn)(CUtensorMap*, CUtensorMapDataType, cuuint32_t, void*, const cuuint64_t*, const cuuint64_t*,
                             const cuuint32_t*, const cuuint32_t*, CUtensorMapInterleave, CUtensorMapSwizzle,
                             CUtensorMapL2promotion, CUtensorMapFloatOOBfill);

void encode(EncodeFn fn, CUtensorMap* map, const void* base, int rank, const cuuint64_t* dims, const cuuint64_t* strides,
            const cuuint32_t* box, CUtensorMapSwizzle sw) {
  const cuuint32_t es[5] = {1, 1, 1, 1, 1};
  fn(map, CU_TENSOR_MAP_DATA_TYPE_BFLOAT16, rank, const_cast<void*>(base), dims, strides, box, es,
     CU_TENSOR_MAP_INTERLEAVE_NONE, sw, CU_TENSOR_MAP_L2_PROMOTION_L2_256B, CU_TENSOR_MAP_FLOAT_OOB_FILL_NONE);
}

}

extern "C" void kernel_launch(void* const* d_in, const int* in_sizes, int n_in, void* d_out, int out_size) {
  (void)in_sizes; (void)n_in; (void)out_size;
  static Params P;
  static const void* key[6] = {nullptr, nullptr, nullptr, nullptr, nullptr, nullptr};
  const void* cur[6] = {d_in[0], d_in[1], d_in[2], d_in[4], d_in[5], d_out};
  bool same = true;
  for (int i = 0; i < 6; i++) same = same && key[i] == cur[i];
  if (!same) {
    void* fn = nullptr;
    cudaDriverEntryPointQueryResult q;
    cudaGetDriverEntryPoint("cuTensorMapEncodeTiled", &fn, cudaEnableDefault, &q);
    EncodeFn enc = (EncodeFn)fn;
    {
      const cuuint64_t d[4] = {256, 1024, 4, 3}, s[3] = {6144, 512, 2048};
      const cuuint32_t b[4] = {32, 32, 2, 3};
      encode(enc, &P.wqkv, d_in[1], 4, d, s, b, CU_TENSOR_MAP_SWIZZLE_64B);
    }
    {
      const cuuint64_t d[3] = {64, 1024, 56}, s[2] = {kDff * 2, 128};
      const cuuint32_t b3[3] = {64, 32, 3}, b2[3] = {64, 32, 2};
      encode(enc, &P.w1a, d_in[4], 3, d, s, b3, CU_TENSOR_MAP_SWIZZLE_128B);
      encode(enc, &P.w1b, d_in[4], 3, d, s, b2, CU_TENSOR_MAP_SWIZZLE_128B);
    }
    {
      const cuuint64_t d2[3] = {64, kDff, 16}, d1[3] = {64, kD, 16}, s[2] = {kD * 2, 128};
      const cuuint32_t b[3] = {64, 32, 2};
      encode(enc, &P.w2, d_in[5], 3, d2, s, b, CU_TENSOR_MAP_SWIZZLE_128B);
      encode(enc, &P.wo, d_in[2], 3, d1, s, b, CU_TENSOR_MAP_SWIZZLE_128B);
    }
    {
      const cuuint64_t d[2] = {kD, kS}, s[1] = {kD * 2};
      const cuuint32_t bx[2] = {64, 128}, bo[2] = {64, 64};
      encode(enc, &P.x, d_in[0], 2, d, s, bx, CU_TENSOR_MAP_SWIZZLE_128B);
      encode(enc, &P.out, d_out, 2, d, s, bo, CU_TENSOR_MAP_SWIZZLE_128B);
    }
    P.xptr = (const __nv_bfloat16*)d_in[0];
    cudaFuncSetAttribute(fused_block_kernel, cudaFuncAttributeMaxDynamicSharedMemorySize, kSmemBytes);
    for (int i = 0; i < 6; i++) key[i] = cur[i];
  }
  fused_block_kernel<<<kCtas, kThreads, kSmemBytes>>>(P);
}
```

```cpp
#include <cuda_runtime.h>
#include <cuda_bf16.h>
#include <cuda.h>
#include <stdint.h>

#define GD192 1
#define GDOUT GD128
#define MAPV 2
#define PREF 0
#define ONES 1
#define EARLYW 1
#define GD128 1

namespace {

constexpr int kS = 2048, kD = 1024, kDff = 3584;
constexpr int kThreads = 512;
constexpr int kCtas = 128;

constexpr uint32_t kSlot = 40960;
constexpr uint32_t kStageOff = 3 * kSlot;
constexpr uint32_t kOutSlot = 2;
constexpr uint32_t kKvOff = 4 * kSlot + 8192;
constexpr uint32_t kNKv = 5;
constexpr uint32_t kQOff = kKvOff + kNKv * 8192;
constexpr uint32_t kBarOff = kQOff + 2 * 8192;
constexpr uint32_t kOnesOff = kBarOff + 512;
constexpr uint32_t kSmemBytes = kOnesOff + 1024 + 1024;
constexpr uint32_t B_GFULL = 0, B_GEMPTY = 4, B_KVFULL = 8, B_KVEMPTY = 13, B_QFULL = 18, B_QEMPTY = 20, B_GST = 22,
                   B_AST = 24, B_STAT = 28;

__device__ __align__(1024) uint8_t g_xn[16 * 16 * 16384];
__device__ __align__(1024) uint8_t g_q[32 * 2048 * 64];
__device__ __align__(1024) uint8_t g_kv[32 * 32 * 8192];
__device__ __align__(1024) uint8_t g_h[16 * 56 * 16384];
__device__ __align__(1024) uint8_t g_o[16 * 32 * 8192];
__device__ __align__(1024) float2 g_stat[2048];
constexpr int F_XN = 0, F_KV = 16, F_H = 48, F_O = 96, F_DONE = 160, F_COUNT = 161;
__device__ unsigned g_flags[F_COUNT * 32];

__device__ __forceinline__ uint32_t smem_u32(const void* p) { return (uint32_t)__cvta_generic_to_shared(p); }
__device__ __forceinline__ void wgmma_fence() { asm volatile("wgmma.fence.sync.aligned;\n" ::: "memory"); }
__device__ __forceinline__ void wgmma_commit() { asm volatile("wgmma.commit_group.sync.aligned;\n" ::: "memory"); }
template <int N>
__device__ __forceinline__ void wgmma_wait() { asm volatile("wgmma.wait_group.sync.aligned %0;\n" ::"n"(N) : "memory"); }
template <int N>
__device__ __forceinline__ void fence_regs(float (&r)[N]) {
#pragma unroll
  for (int i = 0; i < N; i++) asm volatile("" : "+f"(r[i])::"memory");
}
template <int N>
__device__ __forceinline__ void fence_regs(uint32_t (&r)[N]) {
#pragma unroll
  for (int i = 0; i < N; i++) asm volatile("" : "+r"(r[i])::"memory");
}
__device__ __forceinline__ uint64_t mk_desc(uint32_t lo, uint32_t hi) { return ((uint64_t)hi << 32) | lo; }
__host__ __device__ constexpr uint32_t desc_hi(uint32_t sbo, uint32_t swz) { return (sbo >> 4) | (swz << 30); }
__device__ __forceinline__ uint32_t desc_lo(uint32_t addr, uint32_t lbo) { return ((addr & 0x3FFFF) >> 4) | ((lbo >> 4) << 16); }

__device__ __forceinline__ void mbar_init(uint32_t bar, uint32_t cnt) {
  asm volatile("mbarrier.init.shared::cta.b64 [%0], %1;\n" ::"r"(bar), "r"(cnt) : "memory");
}
__device__ __forceinline__ void mbar_expect_tx(uint32_t bar, uint32_t bytes) {
  asm volatile("mbarrier.arrive.expect_tx.shared::cta.b64 _, [%0], %1;\n" ::"r"(bar), "r"(bytes) : "memory");
}
__device__ __forceinline__ void mbar_arrive(uint32_t bar) {
  asm volatile("mbarrier.arrive.shared::cta.b64 _, [%0];\n" ::"r"(bar) : "memory");
}
__device__ __forceinline__ void mbar_arrive_cta(uint32_t bar, uint32_t cta, uint32_t cnt) {
  asm volatile(
      "{\n.reg .b32 ra;\nmapa.shared::cluster.u32 ra, %0, %1;\nmbarrier.arrive.shared::cluster.b64 _, [ra], %2;\n}\n" ::"r"(bar),
      "r"(cta), "r"(cnt)
      : "memory");
}
__device__ __forceinline__ bool mbar_test(uint32_t bar, uint32_t parity) {
  uint32_t ok;
  asm volatile("{\n.reg .pred p;\nmbarrier.test_wait.parity.shared::cta.b64 p, [%1], %2;\nselp.u32 %0, 1, 0, p;\n}\n"
               : "=r"(ok)
               : "r"(bar), "r"(parity)
               : "memory");
  return ok;
}
__device__ __forceinline__ void mbar_wait(uint32_t bar, uint32_t parity) {
  asm volatile(
      "{\n.reg .pred p, q;\n.reg .u32 it;\nmov.u32 it, 0;\n"
      "LW_%=:\n"
      "mbarrier.try_wait.parity.shared::cta.b64 p, [%0], %1;\n"
      "@p bra LD_%=;\n"
      "add.u32 it, it, 1;\n"
      "setp.lt.u32 q, it, 0x400000;\n"
      "@q bra LW_%=;\n"
      "trap;\n"
      "LD_%=:\n}\n" ::"r"(bar), "r"(parity) : "memory");
}
__device__ __forceinline__ void mbar_wait_sleepy(uint32_t bar, uint32_t parity) {
  asm volatile(
      "{\n.reg .pred p, q;\n.reg .u32 it;\nmov.u32 it, 0;\n"
      "LW_%=:\n"
      "mbarrier.try_wait.parity.shared::cta.b64 p, [%0], %1, 20000;\n"
      "@p bra LD_%=;\n"
      "add.u32 it, it, 1;\n"
      "setp.lt.u32 q, it, 0x400000;\n"
      "@q bra LW_%=;\n"
      "trap;\n"
      "LD_%=:\n}\n" ::"r"(bar), "r"(parity) : "memory");
}
__device__ __forceinline__ uint32_t mapa(uint32_t addr, uint32_t cta) {
  uint32_t r;
  asm("mapa.shared::cluster.u32 %0, %1, %2;\n" : "=r"(r) : "r"(addr), "r"(cta));
  return r;
}
__device__ __forceinline__ void mbar_arrive_cluster_if(uint32_t addr, bool pred) {
  asm volatile("{\n.reg .pred p;\nsetp.ne.u32 p, %1, 0;\n@p mbarrier.arrive.shared::cluster.b64 _, [%0];\n}\n" ::"r"(addr),
               "r"((uint32_t)pred)
               : "memory");
}
__device__ __forceinline__ void flag_wait(const unsigned* f, unsigned target) {
  uint32_t it = 0;
#pragma unroll 1
  while (true) {
    unsigned v;
    asm volatile("ld.acquire.gpu.global.u32 %0, [%1];\n" : "=r"(v) : "l"(f) : "memory");
    if (v >= target) break;
    if (++it > (1u << 22)) asm volatile("trap;");
  }
  asm volatile("fence.proxy.async.global;\n" ::: "memory");
}
__device__ __forceinline__ void flag_add(unsigned* f, unsigned v) {
  asm volatile("red.relaxed.gpu.global.add.u32 [%0], %1;\n" ::"l"(f), "r"(v) : "memory");
}
__device__ __forceinline__ void bulk_g2s(uint32_t dst, const void* src, uint32_t bytes, uint32_t bar) {
  asm volatile("cp.async.bulk.shared::cluster.global.mbarrier::complete_tx::bytes [%0], [%1], %2, [%3];\n" ::"r"(dst),
               "l"(src), "r"(bytes), "r"(bar)
               : "memory");
}
__device__ __forceinline__ void bulk_g2s_mc(uint32_t dst, const void* src, uint32_t bytes, uint32_t bar) {
  asm volatile(
      "cp.async.bulk.shared::cluster.global.mbarrier::complete_tx::bytes.multicast::cluster [%0], [%1], %2, [%3], %4;\n" ::"r"(dst),
      "l"(src), "r"(bytes), "r"(bar), "h"((uint16_t)3)
      : "memory");
}
__device__ __forceinline__ void bulk_s2g(void* dst, uint32_t src, uint32_t bytes) {
  asm volatile("cp.async.bulk.global.shared::cta.bulk_group [%0], [%1], %2;\n" ::"l"(dst), "r"(src), "r"(bytes) : "memory");
}
__device__ __forceinline__ void l2_prefetch(const void* src, uint32_t bytes) {
  asm volatile("cp.async.bulk.prefetch.L2.global [%0], %1;\n" ::"l"(src), "r"(bytes) : "memory");
}
__device__ __forceinline__ void bulk_commit() { asm volatile("cp.async.bulk.commit_group;\n" ::: "memory"); }
__device__ __forceinline__ void bulk_wait_read() { asm volatile("cp.async.bulk.wait_group.read 0;\n" ::: "memory"); }
__device__ __forceinline__ void bulk_wait_all() { asm volatile("cp.async.bulk.wait_group 0;\n" ::: "memory"); }
__device__ __forceinline__ void tma_2d(uint32_t dst, const CUtensorMap* m, int c0, int c1, uint32_t bar) {
  asm volatile(
      "cp.async.bulk.tensor.2d.shared::cluster.global.mbarrier::complete_tx::bytes [%0], [%1, {%3, %4}], [%2];\n" ::"r"(dst),
      "l"((uint64_t)m), "r"(bar), "r"(c0), "r"(c1)
      : "memory");
}
__device__ __forceinline__ void tma_3d_mc(uint32_t dst, const CUtensorMap* m, int c0, int c1, int c2, uint32_t bar) {
  asm volatile(
      "cp.async.bulk.tensor.3d.shared::cluster.global.mbarrier::complete_tx::bytes.multicast::cluster [%0], [%1, {%3, %4, %5}], "
      "[%2], %6;\n" ::"r"(dst),
      "l"((uint64_t)m), "r"(bar), "r"(c0), "r"(c1), "r"(c2), "h"((uint16_t)3)
      : "memory");
}
__device__ __forceinline__ void tma_4d_mc(uint32_t dst, const CUtensorMap* m, int c0, int c1, int c2, int c3, uint32_t bar) {
  asm volatile(
      "cp.async.bulk.tensor.4d.shared::cluster.global.mbarrier::complete_tx::bytes.multicast::cluster [%0], [%1, {%3, %4, %5, "
      "%6}], [%2], %7;\n" ::"r"(dst),
      "l"((uint64_t)m), "r"(bar), "r"(c0), "r"(c1), "r"(c2), "r"(c3), "h"((uint16_t)3)
      : "memory");
}
__device__ __forceinline__ void tma_store_2d(const CUtensorMap* m, uint32_t src, int c0, int c1) {
  asm volatile("cp.async.bulk.tensor.2d.global.shared::cta.bulk_group [%0, {%2, %3}], [%1];\n" ::"l"((uint64_t)m), "r"(src),
               "r"(c0), "r"(c1)
               : "memory");
}
__device__ __forceinline__ void prefetch_map(const CUtensorMap* m) {
  asm volatile("prefetch.tensormap [%0];\n" ::"l"((uint64_t)m) : "memory");
}
__device__ __forceinline__ void fence_async_smem() { asm volatile("fence.proxy.async.shared::cta;\n" ::: "memory"); }
__device__ __forceinline__ void stsm4(uint32_t addr, uint32_t a, uint32_t b, uint32_t c, uint32_t d) {
  asm volatile("stmatrix.sync.aligned.m8n8.x4.shared.b16 [%0], {%1, %2, %3, %4};\n" ::"r"(addr), "r"(a), "r"(b), "r"(c), "r"(d)
               : "memory");
}
__device__ __forceinline__ void ldsm4(uint32_t addr, uint32_t& a, uint32_t& b, uint32_t& c, uint32_t& d) {
  asm volatile("ldmatrix.sync.aligned.m8n8.x4.shared.b16 {%0, %1, %2, %3}, [%4];\n"
               : "=r"(a), "=r"(b), "=r"(c), "=r"(d)
               : "r"(addr)
               : "memory");
}
__device__ __forceinline__ float ex2(float x) {
  float y;
  asm("ex2.approx.ftz.f32 %0, %1;" : "=f"(y) : "f"(x));
  return y;
}
__device__ __forceinline__ uint32_t pack_bf16(float lo, float hi) {
  uint32_t r;
  asm("cvt.rn.bf16x2.f32 %0, %1, %2;" : "=r"(r) : "f"(hi), "f"(lo));
  return r;
}
__device__ __forceinline__ uint32_t pack_bf16_relu(float lo, float hi) {
  uint32_t r;
  asm("cvt.rn.relu.bf16x2.f32 %0, %1, %2;" : "=r"(r) : "f"(hi), "f"(lo));
  return r;
}
__device__ __forceinline__ float bf_lo(uint32_t v) { return __uint_as_float(v << 16); }
__device__ __forceinline__ float bf_hi(uint32_t v) { return __uint_as_float(v & 0xffff0000u); }
__device__ __forceinline__ float bf_round(float x) { return __bfloat162float(__float2bfloat16_rn(x)); }
__device__ __forceinline__ void named_sync(int id) { asm volatile("bar.sync %0, 128;\n" ::"r"(id) : "memory"); }
__device__ __forceinline__ void cluster_arrive() { asm volatile("barrier.cluster.arrive.relaxed.aligned;\n" ::: "memory"); }
__device__ __forceinline__ void cluster_wait() { asm volatile("barrier.cluster.wait.acquire.aligned;\n" ::: "memory"); }
#define TM(cond, idx)
#define TACC(acc, stmt) do { stmt; } while (0)
#define TPUT(cond, idx, v)

template <int TB>
__device__ __forceinline__ void wgmma_ss_n192(float (&d)[96], uint64_t da, uint64_t db, int scale_d) {
  asm volatile(
      "{\n.reg .pred p;\nsetp.ne.b32 p, %98, 0;\n"
      "wgmma.mma_async.sync.aligned.m64n192k16.f32.bf16.bf16 {"
      "%0, %1, %2, %3, %4, %5, %6, %7, %8, %9, %10, %11, %12, %13, %14, %15, "
      "%16, %17, %18, %19, %20, %21, %22, %23, %24, %25, %26, %27, %28, %29, %30, %31, "
      "%32, %33, %34, %35, %36, %37, %38, %39, %40, %41, %42, %43, %44, %45, %46, %47, "
      "%48, %49, %50, %51, %52, %53, %54, %55, %56, %57, %58, %59, %60, %61, %62, %63, "
      "%64, %65, %66, %67, %68, %69, %70, %71, %72, %73, %74, %75, %76, %77, %78, %79, "
      "%80, %81, %82, %83, %84, %85, %86, %87, %88, %89, %90, %91, %92, %93, %94, %95}, %96, %97, p, 1, 1, 0, %99;\n}\n"
      : "+f"(d[0]), "+f"(d[1]), "+f"(d[2]), "+f"(d[3]), "+f"(d[4]), "+f"(d[5]), "+f"(d[6]), "+f"(d[7]),
        "+f"(d[8]), "+f"(d[9]), "+f"(d[10]), "+f"(d[11]), "+f"(d[12]), "+f"(d[13]), "+f"(d[14]), "+f"(d[15]),
        "+f"(d[16]), "+f"(d[17]), "+f"(d[18]), "+f"(d[19]), "+f"(d[20]), "+f"(d[21]), "+f"(d[22]), "+f"(d[23]),
        "+f"(d[24]), "+f"(d[25]), "+f"(d[26]), "+f"(d[27]), "+f"(d[28]), "+f"(d[29]), "+f"(d[30]), "+f"(d[31]),
        "+f"(d[32]), "+f"(d[33]), "+f"(d[34]), "+f"(d[35]), "+f"(d[36]), "+f"(d[37]), "+f"(d[38]), "+f"(d[39]),
        "+f"(d[40]), "+f"(d[41]), "+f"(d[42]), "+f"(d[43]), "+f"(d[44]), "+f"(d[45]), "+f"(d[46]), "+f"(d[47]),
        "+f"(d[48]), "+f"(d[49]), "+f"(d[50]), "+f"(d[51]), "+f"(d[52]), "+f"(d[53]), "+f"(d[54]), "+f"(d[55]),
        "+f"(d[56]), "+f"(d[57]), "+f"(d[58]), "+f"(d[59]), "+f"(d[60]), "+f"(d[61]), "+f"(d[62]), "+f"(d[63]),
        "+f"(d[64]), "+f"(d[65]), "+f"(d[66]), "+f"(d[67]), "+f"(d[68]), "+f"(d[69]), "+f"(d[70]), "+f"(d[71]),
        "+f"(d[72]), "+f"(d[73]), "+f"(d[74]), "+f"(d[75]), "+f"(d[76]), "+f"(d[77]), "+f"(d[78]), "+f"(d[79]),
        "+f"(d[80]), "+f"(d[81]), "+f"(d[82]), "+f"(d[83]), "+f"(d[84]), "+f"(d[85]), "+f"(d[86]), "+f"(d[87]),
        "+f"(d[88]), "+f"(d[89]), "+f"(d[90]), "+f"(d[91]), "+f"(d[92]), "+f"(d[93]), "+f"(d[94]), "+f"(d[95])
      : "l"(da), "l"(db), "r"(scale_d), "n"(TB));
}
template <int TB>
__device__ __forceinline__ void wgmma_ss_n160(float (&d)[96], uint64_t da, uint64_t db, int scale_d) {
  asm volatile(
      "{\n.reg .pred p;\nsetp.ne.b32 p, %82, 0;\n"
      "wgmma.mma_async.sync.aligned.m64n160k16.f32.bf16.bf16 {"
      "%0, %1, %2, %3, %4, %5, %6, %7, %8, %9, %10, %11, %12, %13, %14, %15, "
      "%16, %17, %18, %19, %20, %21, %22, %23, %24, %25, %26, %27, %28, %29, %30, %31, "
      "%32, %33, %34, %35, %36, %37, %38, %39, %40, %41, %42, %43, %44, %45, %46, %47, "
      "%48, %49, %50, %51, %52, %53, %54, %55, %56, %57, %58, %59, %60, %61, %62, %63, "
      "%64, %65, %66, %67, %68, %69, %70, %71, %72, %73, %74, %75, %76, %77, %78, %79}, %80, %81, p, 1, 1, 0, %83;\n}\n"
      : "+f"(d[0]), "+f"(d[1]), "+f"(d[2]), "+f"(d[3]), "+f"(d[4]), "+f"(d[5]), "+f"(d[6]), "+f"(d[7]),
        "+f"(d[8]), "+f"(d[9]), "+f"(d[10]), "+f"(d[11]), "+f"(d[12]), "+f"(d[13]), "+f"(d[14]), "+f"(d[15]),
        "+f"(d[16]), "+f"(d[17]), "+f"(d[18]), "+f"(d[19]), "+f"(d[20]), "+f"(d[21]), "+f"(d[22]), "+f"(d[23]),
        "+f"(d[24]), "+f"(d[25]), "+f"(d[26]), "+f"(d[27]), "+f"(d[28]), "+f"(d[29]), "+f"(d[30]), "+f"(d[31]),
        "+f"(d[32]), "+f"(d[33]), "+f"(d[34]), "+f"(d[35]), "+f"(d[36]), "+f"(d[37]), "+f"(d[38]), "+f"(d[39]),
        "+f"(d[40]), "+f"(d[41]), "+f"(d[42]), "+f"(d[43]), "+f"(d[44]), "+f"(d[45]), "+f"(d[46]), "+f"(d[47]),
        "+f"(d[48]), "+f"(d[49]), "+f"(d[50]), "+f"(d[51]), "+f"(d[52]), "+f"(d[53]), "+f"(d[54]), "+f"(d[55]),
        "+f"(d[56]), "+f"(d[57]), "+f"(d[58]), "+f"(d[59]), "+f"(d[60]), "+f"(d[61]), "+f"(d[62]), "+f"(d[63]),
        "+f"(d[64]), "+f"(d[65]), "+f"(d[66]), "+f"(d[67]), "+f"(d[68]), "+f"(d[69]), "+f"(d[70]), "+f"(d[71]),
        "+f"(d[72]), "+f"(d[73]), "+f"(d[74]), "+f"(d[75]), "+f"(d[76]), "+f"(d[77]), "+f"(d[78]), "+f"(d[79])
      : "l"(da), "l"(db), "r"(scale_d), "n"(TB));
}
template <int TB>
__device__ __forceinline__ void wgmma_ss_n128(float (&d)[96], uint64_t da, uint64_t db, int scale_d) {
  asm volatile(
      "{\n.reg .pred p;\nsetp.ne.b32 p, %66, 0;\n"
      "wgmma.mma_async.sync.aligned.m64n128k16.f32.bf16.bf16 {"
      "%0, %1, %2, %3, %4, %5, %6, %7, %8, %9, %10, %11, %12, %13, %14, %15, "
      "%16, %17, %18, %19, %20, %21, %22, %23, %24, %25, %26, %27, %28, %29, %30, %31, "
      "%32, %33, %34, %35, %36, %37, %38, %39, %40, %41, %42, %43, %44, %45, %46, %47, "
      "%48, %49, %50, %51, %52, %53, %54, %55, %56, %57, %58, %59, %60, %61, %62, %63}, %64, %65, p, 1, 1, 0, %67;\n}\n"
      : "+f"(d[0]), "+f"(d[1]), "+f"(d[2]), "+f"(d[3]), "+f"(d[4]), "+f"(d[5]), "+f"(d[6]), "+f"(d[7]),
        "+f"(d[8]), "+f"(d[9]), "+f"(d[10]), "+f"(d[11]), "+f"(d[12]), "+f"(d[13]), "+f"(d[14]), "+f"(d[15]),
        "+f"(d[16]), "+f"(d[17]), "+f"(d[18]), "+f"(d[19]), "+f"(d[20]), "+f"(d[21]), "+f"(d[22]), "+f"(d[23]),
        "+f"(d[24]), "+f"(d[25]), "+f"(d[26]), "+f"(d[27]), "+f"(d[28]), "+f"(d[29]), "+f"(d[30]), "+f"(d[31]),
        "+f"(d[32]), "+f"(d[33]), "+f"(d[34]), "+f"(d[35]), "+f"(d[36]), "+f"(d[37]), "+f"(d[38]), "+f"(d[39]),
        "+f"(d[40]), "+f"(d[41]), "+f"(d[42]), "+f"(d[43]), "+f"(d[44]), "+f"(d[45]), "+f"(d[46]), "+f"(d[47]),
        "+f"(d[48]), "+f"(d[49]), "+f"(d[50]), "+f"(d[51]), "+f"(d[52]), "+f"(d[53]), "+f"(d[54]), "+f"(d[55]),
        "+f"(d[56]), "+f"(d[57]), "+f"(d[58]), "+f"(d[59]), "+f"(d[60]), "+f"(d[61]), "+f"(d[62]), "+f"(d[63])
      : "l"(da), "l"(db), "r"(scale_d), "n"(TB));
}
template <int TB>
__device__ __forceinline__ void wgmma_ss_n96(float (&d)[96], uint64_t da, uint64_t db, int scale_d) {
  asm volatile(
      "{\n.reg .pred p;\nsetp.ne.b32 p, %50, 0;\n"
      "wgmma.mma_async.sync.aligned.m64n96k16.f32.bf16.bf16 {"
      "%0, %1, %2, %3, %4, %5, %6, %7, %8, %9, %10, %11, %12, %13, %14, %15, "
      "%16, %17, %18, %19, %20, %21, %22, %23, %24, %25, %26, %27, %28, %29, %30, %31, "
      "%32, %33, %34, %35, %36, %37, %38, %39, %40, %41, %42, %43, %44, %45, %46, %47}, %48, %49, p, 1, 1, 0, %51;\n}\n"
      : "+f"(d[0]), "+f"(d[1]), "+f"(d[2]), "+f"(d[3]), "+f"(d[4]), "+f"(d[5]), "+f"(d[6]), "+f"(d[7]),
        "+f"(d[8]), "+f"(d[9]), "+f"(d[10]), "+f"(d[11]), "+f"(d[12]), "+f"(d[13]), "+f"(d[14]), "+f"(d[15]),
        "+f"(d[16]), "+f"(d[17]), "+f"(d[18]), "+f"(d[19]), "+f"(d[20]), "+f"(d[21]), "+f"(d[22]), "+f"(d[23]),
        "+f"(d[24]), "+f"(d[25]), "+f"(d[26]), "+f"(d[27]), "+f"(d[28]), "+f"(d[29]), "+f"(d[30]), "+f"(d[31]),
        "+f"(d[32]), "+f"(d[33]), "+f"(d[34]), "+f"(d[35]), "+f"(d[36]), "+f"(d[37]), "+f"(d[38]), "+f"(d[39]),
        "+f"(d[40]), "+f"(d[41]), "+f"(d[42]), "+f"(d[43]), "+f"(d[44]), "+f"(d[45]), "+f"(d[46]), "+f"(d[47])
      : "l"(da), "l"(db), "r"(scale_d), "n"(TB));
}
template <int TB>
__device__ __forceinline__ void wgmma_ss_n64(float (&d)[32], uint64_t da, uint64_t db, int scale_d) {
  asm volatile(
      "{\n.reg .pred p;\nsetp.ne.b32 p, %34, 0;\n"
      "wgmma.mma_async.sync.aligned.m64n64k16.f32.bf16.bf16 {"
      "%0, %1, %2, %3, %4, %5, %6, %7, %8, %9, %10, %11, %12, %13, %14, %15, "
      "%16, %17, %18, %19, %20, %21, %22, %23, %24, %25, %26, %27, %28, %29, %30, %31}, %32, %33, p, 1, 1, 0, %35;\n}\n"
      : "+f"(d[0]), "+f"(d[1]), "+f"(d[2]), "+f"(d[3]), "+f"(d[4]), "+f"(d[5]), "+f"(d[6]), "+f"(d[7]),
        "+f"(d[8]), "+f"(d[9]), "+f"(d[10]), "+f"(d[11]), "+f"(d[12]), "+f"(d[13]), "+f"(d[14]), "+f"(d[15]),
        "+f"(d[16]), "+f"(d[17]), "+f"(d[18]), "+f"(d[19]), "+f"(d[20]), "+f"(d[21]), "+f"(d[22]), "+f"(d[23]),
        "+f"(d[24]), "+f"(d[25]), "+f"(d[26]), "+f"(d[27]), "+f"(d[28]), "+f"(d[29]), "+f"(d[30]), "+f"(d[31])
      : "l"(da), "l"(db), "r"(scale_d), "n"(TB));
}
template <int TB>
__device__ __forceinline__ void wgmma_rs_n32(float (&d)[16], uint32_t a0, uint32_t a1, uint32_t a2, uint32_t a3,
                                             uint64_t db, int scale_d) {
  asm volatile(
      "{\n.reg .pred p;\nsetp.ne.b32 p, %21, 0;\n"
      "wgmma.mma_async.sync.aligned.m64n32k16.f32.bf16.bf16 {"
      "%0, %1, %2, %3, %4, %5, %6, %7, %8, %9, %10, %11, %12, %13, %14, %15}, {%16, %17, %18, %19}, %20, p, 1, 1, %22;\n}\n"
      : "+f"(d[0]), "+f"(d[1]), "+f"(d[2]), "+f"(d[3]), "+f"(d[4]), "+f"(d[5]), "+f"(d[6]), "+f"(d[7]),
        "+f"(d[8]), "+f"(d[9]), "+f"(d[10]), "+f"(d[11]), "+f"(d[12]), "+f"(d[13]), "+f"(d[14]), "+f"(d[15])
      : "r"(a0), "r"(a1), "r"(a2), "r"(a3), "l"(db), "r"(scale_d), "n"(TB));
}
template <int TB>
__device__ __forceinline__ void wgmma_rs_n40(float (&d)[20], uint32_t a0, uint32_t a1, uint32_t a2, uint32_t a3,
                                             uint64_t db, int scale_d) {
  asm volatile(
      "{\n.reg .pred p;\nsetp.ne.b32 p, %25, 0;\n"
      "wgmma.mma_async.sync.aligned.m64n40k16.f32.bf16.bf16 {"
      "%0, %1, %2, %3, %4, %5, %6, %7, %8, %9, %10, %11, %12, %13, %14, %15, "
      "%16, %17, %18, %19}, {%20, %21, %22, %23}, %24, p, 1, 1, %26;\n}\n"
      : "+f"(d[0]), "+f"(d[1]), "+f"(d[2]), "+f"(d[3]), "+f"(d[4]), "+f"(d[5]), "+f"(d[6]), "+f"(d[7]),
        "+f"(d[8]), "+f"(d[9]), "+f"(d[10]), "+f"(d[11]), "+f"(d[12]), "+f"(d[13]), "+f"(d[14]), "+f"(d[15]),
        "+f"(d[16]), "+f"(d[17]), "+f"(d[18]), "+f"(d[19])
      : "r"(a0), "r"(a1), "r"(a2), "r"(a3), "l"(db), "r"(scale_d), "n"(TB));
}

template <int N>
__device__ __forceinline__ void wgmma_gemm(float (&d)[96], uint64_t da, uint64_t db, int sc) {
  if constexpr (N == 192) wgmma_ss_n192<1>(d, da, db, sc);
  else if constexpr (N == 160) wgmma_ss_n160<1>(d, da, db, sc);
  else if constexpr (N == 128) wgmma_ss_n128<1>(d, da, db, sc);
  else wgmma_ss_n96<1>(d, da, db, sc);
}

__device__ __forceinline__ uint32_t next_slot(int pos, bool first_tile, uint32_t& r3) {
  const bool x = (pos & 3) == 3 && (first_tile || pos >= 7);
  const uint32_t s = x ? 3u : r3;
  r3 = x ? r3 : ((r3 == 2) ? 0u : r3 + 1);
  return s;
}
__device__ __forceinline__ bool out_kb_is_attn(int kb) { return (kb >= 32 && kb < 40) || kb >= 64; }

#define GWAIT(bar, par) do { if (!ready) mbar_wait(bar, par); } while (0)
template <int N, int NKB, int GD, bool OUTK>
__device__ __forceinline__ void gemm_mainloop(float (&d0)[96], float (&d1)[96], uint32_t lo0, uint32_t bars, uint32_t& phases,
                                              uint32_t& r3, uint32_t b_lbo, uint32_t b_hi, uint32_t b_k1, uint32_t b_k2,
                                              uint32_t rel_addr, bool rel_lane, uint32_t& twait) {
  const uint32_t a_c = lo0 + (1u << 16), b_c = lo0 + (16384 >> 4) + ((b_lbo >> 4) << 16);
  uint32_t s = next_slot(0, false, r3), rel = 0;
  uint32_t a_lo = a_c + s * (kSlot >> 4), b_lo = b_c + s * (kSlot >> 4);
  uint32_t a_hi = desc_hi(1024, 1), a_half = 8192 >> 4, a_k2 = 64 >> 4;
  bool ready = false, do_rel = false;
#pragma unroll 1
  for (int kb = 0; kb < NKB; kb++) {
    GWAIT(bars + (B_GFULL + s) * 8, (phases >> s) & 1);
    const uint32_t ca_lo = a_lo, cb_lo = b_lo, ca_hi = a_hi, ca_half = a_half, ca_k2 = a_k2;
    wgmma_fence();
#pragma unroll
    for (int k = 0; k < 4; k++) {
      const uint64_t db = mk_desc(cb_lo + (k >> 1) * b_k2 + (k & 1) * b_k1, b_hi);
      const uint32_t ak = ca_lo + (k >> 1) * ca_k2 + (k & 1) * 2;
      const int sc = (k > 0) ? 1 : (kb > 0);
      wgmma_wait<GD>();
      wgmma_gemm<N>(d0, mk_desc(ak, ca_hi), db, sc);
      wgmma_commit();
      if (2 * k == GD) mbar_arrive_cluster_if(rel, do_rel);
      wgmma_wait<GD>();
      wgmma_gemm<N>(d1, mk_desc(ak + ca_half, ca_hi), db, sc);
      wgmma_commit();
      if (2 * k + 1 == GD) mbar_arrive_cluster_if(rel, do_rel);
      if (k == 2) {
        phases ^= 1u << s;
        rel = rel_addr + s * 8;
        do_rel = rel_lane;
        uint32_t r3n = r3;
        const uint32_t sn = next_slot(kb + 1, false, r3n);
        if (kb + 1 < NKB) { s = sn; r3 = r3n; }
        a_lo = a_c + s * (kSlot >> 4);
        b_lo = b_c + s * (kSlot >> 4);
        if (OUTK) {
          const bool at = out_kb_is_attn(kb + 1);
          a_hi = at ? desc_hi(512, 2) : desc_hi(1024, 1);
          a_half = at ? 4096 >> 4 : 8192 >> 4;
          a_k2 = at ? 8192 >> 4 : 64 >> 4;
        }
        ready = mbar_test(bars + (B_GFULL + s) * 8, (phases >> s) & 1);
      }
    }
  }
  wgmma_wait<0>();
  fence_regs(d0);
  fence_regs(d1);
}

__device__ __forceinline__ void gemm_first(float (&d0)[96], float (&d1)[96], float (&cs)[3], uint32_t sb, uint32_t bars,
                                           uint32_t rank, uint32_t rel_addr, bool rel_lane, uint32_t& twait) {
  const int lane = threadIdx.x & 31, w = (threadIdx.x >> 5) & 3;
  const uint32_t a_lo0 = desc_lo(sb, 16), b_lo0 = desc_lo(sb + 16384, 2048);
  bool ready = false;
#pragma unroll 1
  for (int kb = 0; kb < 16; kb++) {
    const uint32_t s = kb & 3;
    GWAIT(bars + (B_GFULL + s) * 8, (kb >> 2) & 1);
    const uint32_t a_lo = a_lo0 + s * (kSlot >> 4), b_lo = b_lo0 + s * (kSlot >> 4);
    wgmma_fence();
#pragma unroll
    for (int k = 0; k < 4; k++) {
      const uint64_t db = mk_desc(b_lo + (k >> 1) * (6144 >> 4) + (k & 1) * (1024 >> 4), desc_hi(512, 2));
      const int sc = (k > 0) ? 1 : (kb > 0);
      wgmma_ss_n96<1>(d0, mk_desc(a_lo + 2 * k, desc_hi(1024, 1)), db, sc);
      wgmma_ss_n96<1>(d1, mk_desc(a_lo + 2 * k + (8192 >> 4), desc_hi(1024, 1)), db, sc);
    }
    wgmma_commit();
    wgmma_wait<1>();
    mbar_arrive_cluster_if(rel_addr + ((s + 3) & 3) * 8, rel_lane && kb > 0);
    uint32_t bq[3][4];
#pragma unroll
    for (int i = 0; i < 3; i++) {
      const int nb = 3 * w + i;
      asm volatile("ldmatrix.sync.aligned.m8n8.x4.trans.shared.b16 {%0, %1, %2, %3}, [%4];\n"
                   : "=r"(bq[i][0]), "=r"(bq[i][1]), "=r"(bq[i][2]), "=r"(bq[i][3])
                   : "r"(sb + s * kSlot + 16384 + rank * 6144 + (nb >> 2) * 2048 + lane * 64 + (((nb & 3) ^ ((lane >> 1) & 3)) << 4)));
    }
#pragma unroll
    for (int i = 0; i < 3; i++)
      cs[i] += ((bf_lo(bq[i][0]) + bf_hi(bq[i][0])) + (bf_lo(bq[i][1]) + bf_hi(bq[i][1]))) +
               ((bf_lo(bq[i][2]) + bf_hi(bq[i][2])) + (bf_lo(bq[i][3]) + bf_hi(bq[i][3])));
    asm volatile("" : "+f"(cs[0]), "+f"(cs[1]), "+f"(cs[2])::"memory");
    ready = mbar_test(bars + (B_GFULL + ((s + 1) & 3)) * 8, ((kb + 1) >> 2) & 1);
  }
  wgmma_wait<0>();
  fence_regs(d0);
  fence_regs(d1);
}

__device__ __forceinline__ void epi_publish(uint32_t bar, int lane) {
  fence_async_smem();
  __syncwarp();
  if (lane == 0) mbar_arrive(bar);
}
constexpr float kQScale = 0.17677669529663687f * 1.4426950408889634f;
template <int NJ, int NQ>
__device__ __forceinline__ void epi_qkv(const float (&d)[96], uint32_t base, uint32_t sw, uint32_t scol) {
#pragma unroll
  for (int jj = 0; jj < NJ; jj++) {
    const float f = jj < NQ ? kQScale : 1.f;
    stsm4(base + (jj >> 1) * 8192 + ((((jj & 1) * 2 + scol) ^ sw) << 4), pack_bf16(d[8 * jj] * f, d[8 * jj + 1] * f),
          pack_bf16(d[8 * jj + 2] * f, d[8 * jj + 3] * f), pack_bf16(d[8 * jj + 4] * f, d[8 * jj + 5] * f),
          pack_bf16(d[8 * jj + 6] * f, d[8 * jj + 7] * f));
  }
}
__device__ __forceinline__ void epi_qkv_ln(const float (&d)[96], uint32_t cs_addr, float2 s0, float2 s1, uint32_t base,
                                           uint32_t sw, uint32_t scol) {
#pragma unroll
  for (int jj = 0; jj < 6; jj++) {
    const float f0 = jj < 2 ? kQScale * s0.y : s0.y, f1 = jj < 2 ? kQScale * s1.y : s1.y;
    float c[4];
    float e[4];
    asm volatile("ld.shared.v2.f32 {%0, %1}, [%2];\n" : "=f"(c[0]), "=f"(c[1]) : "r"(cs_addr + jj * 64));
    asm volatile("ld.shared.v2.f32 {%0, %1}, [%2];\n" : "=f"(c[2]), "=f"(c[3]) : "r"(cs_addr + jj * 64 + 32));
    asm volatile("ld.shared.v2.f32 {%0, %1}, [%2];\n" : "=f"(e[0]), "=f"(e[1]) : "r"(cs_addr + jj * 64 + 384));
    asm volatile("ld.shared.v2.f32 {%0, %1}, [%2];\n" : "=f"(e[2]), "=f"(e[3]) : "r"(cs_addr + jj * 64 + 416));
#pragma unroll
    for (int i = 0; i < 4; i++) c[i] += e[i];
    float v[8];
#pragma unroll
    for (int i = 0; i < 8; i++) {
      const float ci = c[(i >> 2) * 2 + (i & 1)];
      v[i] = (i & 2) ? fmaf(-s1.x, ci, d[8 * jj + i]) * f1 : fmaf(-s0.x, ci, d[8 * jj + i]) * f0;
    }
    stsm4(base + (jj >> 1) * 8192 + ((((jj & 1) * 2 + scol) ^ sw) << 4), pack_bf16(v[0], v[1]), pack_bf16(v[2], v[3]),
          pack_bf16(v[4], v[5]), pack_bf16(v[6], v[7]));
  }
}
template <int J0, int J1>
__device__ __forceinline__ void epi_relu(const float (&d)[96], uint32_t base, uint32_t sw, uint32_t scol) {
#pragma unroll
  for (int jj = J0; jj < J1; jj++)
    stsm4(base + ((jj - J0) >> 2) * 16384 + (((((jj - J0) & 3) * 2 + scol) ^ sw) << 4), pack_bf16_relu(d[8 * jj], d[8 * jj + 1]),
          pack_bf16_relu(d[8 * jj + 2], d[8 * jj + 3]), pack_bf16_relu(d[8 * jj + 4], d[8 * jj + 5]),
          pack_bf16_relu(d[8 * jj + 6], d[8 * jj + 7]));
}
__device__ __forceinline__ void epi_out(const float (&d)[96], uint32_t base, uint32_t sw, uint32_t scol) {
#pragma unroll
  for (int jj = 0; jj < 8; jj++) {
    const uint32_t a = base + (jj >> 2) * 16384 + ((((jj & 3) * 2 + scol) ^ sw) << 4);
    uint32_t x0, x1, x2, x3;
    ldsm4(a, x0, x1, x2, x3);
    stsm4(a, pack_bf16(d[8 * jj] + bf_lo(x0), d[8 * jj + 1] + bf_hi(x0)), pack_bf16(d[8 * jj + 2] + bf_lo(x1), d[8 * jj + 3] + bf_hi(x1)),
          pack_bf16(d[8 * jj + 4] + bf_lo(x2), d[8 * jj + 5] + bf_hi(x2)), pack_bf16(d[8 * jj + 6] + bf_lo(x3), d[8 * jj + 7] + bf_hi(x3)));
  }
}

__device__ __noinline__ void attn_exact(float* o_out, uint32_t q_smem_row_addr, const uint8_t* kv_head) {
  const int lane = threadIdx.x & 31, g = lane >> 2, t = lane & 3;
  uint32_t qa[2][4];
  {
    const int r = (lane & 7) + ((lane >> 3) & 1) * 8;
#pragma unroll
    for (int k = 0; k < 2; k++) {
      const int c16 = 2 * k + (lane >> 4);
      ldsm4(q_smem_row_addr + r * 64 + ((c16 ^ ((r >> 1) & 3)) << 4), qa[k][0], qa[k][1], qa[k][2], qa[k][3]);
    }
  }
  float o[16];
#pragma unroll
  for (int i = 0; i < 16; i++) o[i] = 0.f;
  float m0 = -INFINITY, m1 = -INFINITY, l0 = 0.f, l1 = 0.f;
#pragma unroll 1
  for (int kc = 0; kc < kS / 16; kc++) {
    const uint8_t* kt = kv_head + (kc >> 2) * 8192;
    const int k0 = (kc & 3) * 16;
    float s[2][4];
#pragma unroll
    for (int nb = 0; nb < 2; nb++) {
      s[nb][0] = s[nb][1] = s[nb][2] = s[nb][3] = 0.f;
      const int key = k0 + nb * 8 + g;
#pragma unroll
      for (int k = 0; k < 2; k++) {
        const uint32_t b0 = __ldcg((const uint32_t*)(kt + key * 64 + (((2 * k) ^ ((key >> 1) & 3)) << 4) + t * 4));
        const uint32_t b1 = __ldcg((const uint32_t*)(kt + key * 64 + (((2 * k + 1) ^ ((key >> 1) & 3)) << 4) + t * 4));
        asm volatile(
            "mma.sync.aligned.m16n8k16.row.col.f32.bf16.bf16.f32 {%0,%1,%2,%3}, {%4,%5,%6,%7}, {%8,%9}, {%0,%1,%2,%3};\n"
            : "+f"(s[nb][0]), "+f"(s[nb][1]), "+f"(s[nb][2]), "+f"(s[nb][3])
            : "r"(qa[k][0]), "r"(qa[k][1]), "r"(qa[k][2]), "r"(qa[k][3]), "r"(b0), "r"(b1));
      }
    }
    float x0 = fmaxf(fmaxf(s[0][0], s[0][1]), fmaxf(s[1][0], s[1][1]));
    float x1 = fmaxf(fmaxf(s[0][2], s[0][3]), fmaxf(s[1][2], s[1][3]));
    x0 = fmaxf(x0, __shfl_xor_sync(~0u, x0, 1)); x1 = fmaxf(x1, __shfl_xor_sync(~0u, x1, 1));
    x0 = fmaxf(x0, __shfl_xor_sync(~0u, x0, 2)); x1 = fmaxf(x1, __shfl_xor_sync(~0u, x1, 2));
    x0 = fmaxf(x0, m0); x1 = fmaxf(x1, m1);
    const float c0 = ex2(m0 - x0), c1 = ex2(m1 - x1);
    m0 = x0; m1 = x1;
    uint32_t p[4];
    {
      const float e00 = ex2(s[0][0] - m0), e01 = ex2(s[0][1] - m0), e02 = ex2(s[0][2] - m1), e03 = ex2(s[0][3] - m1);
      const float e10 = ex2(s[1][0] - m0), e11 = ex2(s[1][1] - m0), e12 = ex2(s[1][2] - m1), e13 = ex2(s[1][3] - m1);
      l0 = l0 * c0 + (e00 + e01 + e10 + e11);
      l1 = l1 * c1 + (e02 + e03 + e12 + e13);
      p[0] = pack_bf16(e00, e01); p[1] = pack_bf16(e02, e03); p[2] = pack_bf16(e10, e11); p[3] = pack_bf16(e12, e13);
    }
    const uint8_t* vt = kt + 4096;
#pragma unroll
    for (int nb = 0; nb < 4; nb++) {
      uint32_t hv[4];
#pragma unroll
      for (int i = 0; i < 4; i++) {
        const int key = k0 + 2 * t + (i & 1) + (i >> 1) * 8;
        hv[i] = __ldcg((const unsigned short*)(vt + key * 64 + ((nb ^ ((key >> 1) & 3)) << 4) + g * 2));
      }
      const uint32_t b0 = hv[0] | (hv[1] << 16), b1 = hv[2] | (hv[3] << 16);
      o[4 * nb] *= c0; o[4 * nb + 1] *= c0; o[4 * nb + 2] *= c1; o[4 * nb + 3] *= c1;
      asm volatile(
          "mma.sync.aligned.m16n8k16.row.col.f32.bf16.bf16.f32 {%0,%1,%2,%3}, {%4,%5,%6,%7}, {%8,%9}, {%0,%1,%2,%3};\n"
          : "+f"(o[4 * nb]), "+f"(o[4 * nb + 1]), "+f"(o[4 * nb + 2]), "+f"(o[4 * nb + 3])
          : "r"(p[0]), "r"(p[1]), "r"(p[2]), "r"(p[3]), "r"(b0), "r"(b1));
    }
  }
  l0 += __shfl_xor_sync(~0u, l0, 1); l1 += __shfl_xor_sync(~0u, l1, 1);
  l0 += __shfl_xor_sync(~0u, l0, 2); l1 += __shfl_xor_sync(~0u, l1, 2);
  const float i0 = 1.f / l0, i1 = 1.f / l1;
#pragma unroll
  for (int nb = 0; nb < 4; nb++) {
    o_out[4 * nb] = o[4 * nb] * i0; o_out[4 * nb + 1] = o[4 * nb + 1] * i0;
    o_out[4 * nb + 2] = o[4 * nb + 2] * i1; o_out[4 * nb + 3] = o[4 * nb + 3] * i1;
  }
}

struct Params {
  CUtensorMap wqkv1, wqkv2, w1a, w1c, w2, wo, x, out;
  const __nv_bfloat16* xptr;
  const uint8_t *wqkv_p, *w1_p, *w2_p, *wo_p;
};

__global__ void __cluster_dims__(2, 1, 1) __launch_bounds__(kThreads, 1) fused_block_kernel(const __grid_constant__ Params P) {
  extern __shared__ __align__(1024) uint8_t smem_raw[];
  const uint32_t sb = (smem_u32(smem_raw) + 1023) & ~1023u;
  const uint32_t bars = sb + kBarOff;
  const int warp = __shfl_sync(~0u, threadIdx.x >> 5, 0);
  const int lane = threadIdx.x & 31;
  const uint32_t rank = blockIdx.x & 1;
  const int cl = blockIdx.x >> 1;
  const int c = ((cl & 1) << 2) | ((cl >> 3) & 3);
  const int m = (((cl & 6) | (cl >> 5)) << 1) + rank;
  TM(threadIdx.x == 0, 0);

  if (threadIdx.x == 0) {
    for (int i = 0; i < 4; i++) { mbar_init(bars + (B_GFULL + i) * 8, 1); mbar_init(bars + (B_GEMPTY + i) * 8, 8); }
    for (int i = 0; i < (int)kNKv; i++) { mbar_init(bars + (B_KVFULL + i) * 8, 1); mbar_init(bars + (B_KVEMPTY + i) * 8, 16); }
    for (int i = 0; i < 2; i++) { mbar_init(bars + (B_QFULL + i) * 8, 1); mbar_init(bars + (B_QEMPTY + i) * 8, 1); mbar_init(bars + (B_GST + i) * 8, 4); }
    for (int i = 0; i < 4; i++) mbar_init(bars + (B_AST + i) * 8, 4);
    mbar_init(bars + B_STAT * 8, 1);
    asm volatile("fence.mbarrier_init.release.cluster;\n" ::: "memory");
  }
  if (ONES && threadIdx.x >= 256) {
    asm volatile("st.shared.b32 [%0], %1;\n" ::"r"(sb + kOnesOff + (threadIdx.x - 256) * 4), "r"(0x3f803f80u) : "memory");
    fence_async_smem();
  }
  __syncthreads();
  cluster_arrive();

  if (warp < 4) {
    asm volatile("setmaxnreg.dec.sync.aligned.u32 40;\n");
    if (warp == 1 && lane == 0) { prefetch_map(&P.wqkv1); prefetch_map(&P.wqkv2); prefetch_map(&P.w1c); prefetch_map(&P.w1a); prefetch_map(&P.w2); prefetch_map(&P.wo); }
    if (warp == 0 && lane == 0) {
      for (int s = 0; s < 4; s++) {
        mbar_expect_tx(bars + (B_GFULL + s) * 8, 16384 + 12288);
        tma_2d(sb + s * kSlot, &P.x, s * 64, 128 * m, bars + (B_GFULL + s) * 8);
      }
    }
    if (warp == 2 && lane == 0) prefetch_map(&P.out);
    __syncwarp();
    cluster_wait();
    if (lane == 0) {
      if (warp == 0) {
        uint32_t ph = 0xf, r3 = 0;
        const uint8_t* xn = g_xn + (size_t)m * 16 * 16384;
#pragma unroll 1
        for (int i = 0; i < 80; i++) {
          const int t = i >> 4, kb = i & 15;
          const uint32_t s = next_slot(kb, t == 0, r3), full = bars + (B_GFULL + s) * 8, dst = sb + s * kSlot;
          mbar_wait_sleepy(bars + (B_GEMPTY + s) * 8, (ph >> s) & 1);
          ph ^= 1u << s;
          const int krow = kb * 64 + rank * 32;
          if (t == 0) {
            if (i >= 4) mbar_expect_tx(full, 16384 + 12288);
            tma_4d_mc(dst + 16384 + rank * 6144, &P.wqkv1, 32 * c, krow, 0, 0, full);
            if (i >= 4) tma_2d(dst, &P.x, kb * 64, 128 * m, full);
          } else {
            mbar_expect_tx(full, t == 2 ? 16384 + 20480 : 16384 + 24576);
            if (t == 1) {
              tma_4d_mc(dst + 16384 + rank * 12288, &P.wqkv2, 32 * c, krow, 1, 0, full);
            } else if (t == 2) {
              tma_4d_mc(dst + 16384 + rank * 10240, &P.wqkv1, 32 * c, krow, 3, 0, full);
              tma_3d_mc(dst + 16384 + rank * 10240 + 6144, &P.w1c, 0, krow, 14 * c, full);
            } else {
              tma_3d_mc(dst + 16384 + rank * 12288, &P.w1a, 0, krow, 7 * c + 3 * t - 8, full);
            }
            if (i == 16) { flag_wait(&g_flags[(F_XN + m) * 32], 64); TM(true, 1); }
            bulk_g2s(dst, xn + kb * 16384, 16384, full);
          }
        }
#pragma unroll 1
        for (int i = 0; i <= 72; i++) {
          const uint32_t s = next_slot(i, false, r3), full = bars + (B_GFULL + s) * 8, dst = sb + s * kSlot;
          mbar_wait_sleepy(bars + (B_GEMPTY + s) * 8, (ph >> s) & 1);
          ph ^= 1u << s;
          mbar_expect_tx(full, 32768);
          if (i == 72) {
            tma_2d(dst, &P.x, 128 * c, 128 * m, full);
            tma_2d(dst + 16384, &P.x, 128 * c + 64, 128 * m, full);
          } else if (out_kb_is_attn(i)) {
            const int j = i < 40 ? i - 32 : i - 56;
            tma_3d_mc(dst + 16384 + rank * 8192, &P.wo, 0, j * 64 + rank * 32, 2 * c, full);
            if ((j & 3) == 0) flag_wait(&g_flags[(F_O + m * 4 + (j >> 2)) * 32], 16);
            bulk_g2s(dst, g_o + ((size_t)m * 32 + 2 * j) * 8192, 16384, full);
          } else {
            int hk;
            if (i < 8) hk = 7 * i;
            else if (i < 32) hk = ((i - 8) / 3) * 7 + 1 + (i - 8) % 3;
            else hk = ((i - 40) / 3) * 7 + 4 + (i - 40) % 3;
            tma_3d_mc(dst + 16384 + rank * 8192, &P.w2, 0, hk * 64 + rank * 32, 2 * c, full);
            if (i == 0) flag_wait(&g_flags[(F_H + m * 3 + 0) * 32], 16);
            if (i == 8) flag_wait(&g_flags[(F_H + m * 3 + 1) * 32], 16);
            if (i == 40) flag_wait(&g_flags[(F_H + m * 3 + 2) * 32], 16);
            bulk_g2s(dst, g_h + ((size_t)m * 56 + hk) * 16384, 16384, full);
          }
        }
      } else if (warp == 1) {
        flag_wait(&g_flags[(F_XN + m) * 32], 64);
        mbar_expect_tx(bars + B_STAT * 8, 1024 + 768);
        bulk_g2s(sb + kQOff + 8192, g_stat + m * 128, 1024, bars + B_STAT * 8);
        uint32_t s = 0, ph = 1;
#pragma unroll 1
        for (int g = 0; g <= 128; g++) {
          if ((g & 31) == 0 && g < 128) {
            const int u = g >> 5, head = 8 * u + c;
            flag_wait(&g_flags[(F_KV + head) * 32], 32);
            TM(true, 2 + u);
            if (u >= 2) mbar_wait_sleepy(bars + (B_QEMPTY + (u & 1)) * 8, 0);
            mbar_expect_tx(bars + (B_QFULL + (u & 1)) * 8, 8192);
            bulk_g2s(sb + kQOff + (u & 1) * 8192, g_q + ((size_t)head * kS + m * 128) * 64, 8192, bars + (B_QFULL + (u & 1)) * 8);
          }
          const int t = rank ? max(g - 1, 0) : min(g, 127);
          const uint8_t* src = g_kv + (size_t)((8 * (t >> 5) + c) * 32 + (t & 31)) * 8192 + rank * 4096;
          mbar_wait_sleepy(bars + (B_KVEMPTY + s) * 8, ph);
          mbar_expect_tx(bars + (B_KVFULL + s) * 8, 8192);
          bulk_g2s_mc(sb + kKvOff + s * 8192 + rank * 4096, src, 4096, bars + (B_KVFULL + s) * 8);
          if (++s == kNKv) { s = 0; ph ^= 1; }
        }
      } else if (warp == 2) {
        const uint32_t st = sb + kStageOff;
#pragma unroll 1
        for (int t = 0; t < 5; t++) {
#pragma unroll 1
          for (int h = 0; h < 2; h++) {
            mbar_wait_sleepy(bars + (B_GST + h) * 8, t & 1);
            if (t < 3) {
              const int nr = t == 1 ? 2 : 1;
              for (int r = 0; r < nr; r++) {
                const int head = 8 * (t == 2 ? 3 : t + r) + c;
                bulk_s2g(g_q + ((size_t)head * kS + m * 128 + h * 64) * 64, st + r * 8192 + h * 4096, 4096);
                uint8_t* kv = g_kv + ((size_t)head * 32 + 2 * m + h) * 8192;
                bulk_s2g(kv, st + (nr + r) * 8192 + h * 4096, 4096);
                bulk_s2g(kv + 4096, st + (2 * nr + r) * 8192 + h * 4096, 4096);
              }
              if (t == 2) bulk_s2g(g_h + ((size_t)m * 56 + 7 * c) * 16384 + h * 8192, st + 24576 + h * 8192, 8192);
            } else {
              for (int a = 0; a < 3; a++)
                bulk_s2g(g_h + ((size_t)m * 56 + 7 * c + 3 * t - 8 + a) * 16384 + h * 8192, st + a * 16384 + h * 8192, 8192);
            }
            bulk_commit();
          }
          bulk_wait_read();
          TM(t < 2, 52 + 2 * t);
          mbar_arrive_cta(bars + (B_GEMPTY + 3) * 8, 0, 4);
          mbar_arrive_cta(bars + (B_GEMPTY + 3) * 8, 1, 4);
          bulk_wait_all();
          TM(t < 2, 53 + 2 * t);
          if (t < 3) flag_add(&g_flags[(F_KV + 8 * (t == 2 ? 3 : t) + c) * 32], 2);
          if (t == 1) flag_add(&g_flags[(F_KV + 16 + c) * 32], 2);
          if (t >= 2) flag_add(&g_flags[(F_H + m * 3 + t - 2) * 32], 2);
          TM(true, 8 + t);
        }
#pragma unroll 1
        for (int h = 0; h < 2; h++) {
          mbar_wait_sleepy(bars + (B_GST + h) * 8, 1);
          tma_store_2d(&P.out, sb + kOutSlot * kSlot + h * 8192, 128 * c, 128 * m + 64 * h);
          tma_store_2d(&P.out, sb + kOutSlot * kSlot + 16384 + h * 8192, 128 * c + 64, 128 * m + 64 * h);
          bulk_commit();
        }
        bulk_wait_all();
        TM(true, 13);
      } else {
        if (PREF & 1) {
          for (int i = 0; i < 6; i++) l2_prefetch(P.wqkv_p + (size_t)blockIdx.x * 49152 + i * 8192, 8192);
          for (int i = 0; i < 7; i++) l2_prefetch(P.w1_p + (size_t)blockIdx.x * 57344 + i * 8192, 8192);
        }
#pragma unroll 1
        for (int u = 0; u < 4; u++) {
          for (int w = 0; w < 2; w++) {
            mbar_wait_sleepy(bars + (B_AST + w * 2 + (u & 1)) * 8, u >> 1);
            bulk_s2g(g_o + ((size_t)m * 32 + 8 * u + c) * 8192 + w * 4096, sb + kQOff + (u & 1) * 8192 + w * 4096, 4096);
            bulk_commit();
          }
          bulk_wait_read();
          mbar_arrive(bars + (B_QEMPTY + (u & 1)) * 8);
          bulk_wait_all();
          flag_add(&g_flags[(F_O + m * 4 + u) * 32], 2);
          TM(true, 14 + u);
          if ((PREF & 2) && u == 0) {
            for (int i = 0; i < 7; i++) l2_prefetch(P.w2_p + (size_t)blockIdx.x * 57344 + i * 8192, 8192);
            for (int i = 0; i < 2; i++) l2_prefetch(P.wo_p + (size_t)blockIdx.x * 16384 + i * 8192, 8192);
          }
        }
      }
    }
    __syncwarp();
  } else if (warp < 8) {
    asm volatile("setmaxnreg.inc.sync.aligned.u32 240;\n");
    cluster_wait();
    const int w = warp & 3;
    const bool rel_lane = lane < 2;
    const uint32_t rel_addr = mapa(bars + B_GEMPTY * 8, lane & 1);
    uint32_t phases = 0, r3 = 0, twait = 0;
    uint32_t lo0 = (sb & 0x3FFFF) >> 4;
    asm volatile("" : "+r"(lo0));
    lo0 = __shfl_sync(~0u, lo0, 0);
    const uint32_t srow = w * 16 + (lane & 7) + ((lane >> 3) & 1) * 8, scol = lane >> 4;
    const uint32_t st = sb + kStageOff;
    const uint32_t gst0 = bars + B_GST * 8, gst1 = gst0 + 8;
    const uint32_t b64 = st + srow * 64, sw64 = (srow >> 1) & 3, b128 = srow * 128, sw128 = srow & 7;
    float d0[96], d1[96], cs[3] = {0.f, 0.f, 0.f};
#pragma unroll
    for (int i = 0; i < 96; i++) { d0[i] = 0.f; d1[i] = 0.f; }
    gemm_first(d0, d1, cs, sb, bars, rank, rel_addr, rel_lane, twait);
    TM(threadIdx.x == 128, 20);
    const uint32_t csb = sb + kQOff + 8192 + 1024;
#pragma unroll
    for (int i = 0; i < 3; i++) {
      cs[i] += __shfl_xor_sync(~0u, cs[i], 1);
      cs[i] += __shfl_xor_sync(~0u, cs[i], 2);
      if ((lane & 3) < 2)
        asm volatile("st.async.weak.shared::cluster.mbarrier::complete_tx::bytes.b32 [%0], %1, [%2];\n" ::"r"(
                         mapa(csb + rank * 384 + ((3 * w + i) * 8 + (lane >> 2)) * 4, lane & 1)),
                     "r"(__float_as_uint(cs[i])), "r"(mapa(bars + B_STAT * 8, lane & 1))
                     : "memory");
    }
    named_sync(1);
    mbar_wait(bars + B_STAT * 8, 0);
    {
      float2 sv[4];
#pragma unroll
      for (int i = 0; i < 4; i++)
        asm volatile("ld.shared.v2.f32 {%0, %1}, [%2];\n" : "=f"(sv[i].x), "=f"(sv[i].y)
                     : "r"(sb + kQOff + 8192 + ((i >> 1) * 64 + w * 16 + (lane >> 2) + (i & 1) * 8) * 8));
      epi_qkv_ln(d0, csb + (lane & 3) * 8, sv[0], sv[1], b64, sw64, scol);
      epi_publish(gst0, lane);
      epi_qkv_ln(d1, csb + (lane & 3) * 8, sv[2], sv[3], b64 + 4096, sw64, scol);
      epi_publish(gst1, lane);
    }
    TM(threadIdx.x == 128, 26);
    gemm_mainloop<192, 16, GD192, false>(d0, d1, lo0, bars, phases, r3, 2048, desc_hi(512, 2), 1024 >> 4, 12288 >> 4, rel_addr, rel_lane, twait);
    TM(threadIdx.x == 128, 21);
    named_sync(1);
    epi_qkv<12, 4>(d0, b64, sw64, scol);
    epi_publish(gst0, lane);
    epi_qkv<12, 4>(d1, b64 + 4096, sw64, scol);
    epi_publish(gst1, lane);
    TM(threadIdx.x == 128, 27);
    gemm_mainloop<160, 16, GD192, false>(d0, d1, lo0, bars, phases, r3, 2048, desc_hi(512, 2), 1024 >> 4, 10240 >> 4, rel_addr, rel_lane, twait);
    TM(threadIdx.x == 128, 22);
    named_sync(1);
    epi_qkv<6, 2>(d0, b64, sw64, scol);
    epi_relu<6, 10>(d0, st + 24576 + b128, sw128, scol);
    epi_publish(gst0, lane);
    epi_qkv<6, 2>(d1, b64 + 4096, sw64, scol);
    epi_relu<6, 10>(d1, st + 24576 + 8192 + b128, sw128, scol);
    epi_publish(gst1, lane);
#pragma unroll 1
    for (int t = 3; t < 5; t++) {
      gemm_mainloop<192, 16, GD192, false>(d0, d1, lo0, bars, phases, r3, 4096, desc_hi(1024, 1), 2048 >> 4, 12288 >> 4, rel_addr, rel_lane, twait);
      TM(threadIdx.x == 128, 20 + t);
      named_sync(1);
      epi_relu<0, 12>(d0, st + b128, sw128, scol);
      epi_publish(gst0, lane);
      epi_relu<0, 12>(d1, st + 8192 + b128, sw128, scol);
      epi_publish(gst1, lane);
    }
    gemm_mainloop<128, 72, GDOUT, true>(d0, d1, lo0, bars, phases, r3, 4096, desc_hi(1024, 1), 2048 >> 4, 8192 >> 4, rel_addr, rel_lane, twait);
    TM(threadIdx.x == 128, 25);
    mbar_wait(bars + (B_GFULL + kOutSlot) * 8, (phases >> kOutSlot) & 1);
    epi_out(d0, sb + kOutSlot * kSlot + b128, sw128, scol);
    epi_publish(gst0, lane);
    epi_out(d1, sb + kOutSlot * kSlot + 8192 + b128, sw128, scol);
    epi_publish(gst1, lane);
  } else {
    asm volatile("setmaxnreg.dec.sync.aligned.u32 112;\n");
    {
      const int r0 = c * 16 + (warp - 8) * 2;
      const uint32_t lnbuf = sb + kKvOff + (warp - 8) * 4096;
      const uint32_t statbuf = sb + kKvOff + 32768 + (warp - 8) * 16;
      uint4 v[2][4];
#pragma unroll
      for (int i = 0; i < 2; i++)
#pragma unroll
        for (int j = 0; j < 4; j++)
          v[i][j] = __ldg(reinterpret_cast<const uint4*>(P.xptr + (size_t)(m * 128 + r0 + i) * kD) + lane + 32 * j);
      TM(threadIdx.x == 256, 56);
#pragma unroll
      for (int i = 0; i < 2; i++) {
        float f[32];
#pragma unroll
        for (int j = 0; j < 4; j++) {
          f[8 * j] = bf_lo(v[i][j].x); f[8 * j + 1] = bf_hi(v[i][j].x); f[8 * j + 2] = bf_lo(v[i][j].y); f[8 * j + 3] = bf_hi(v[i][j].y);
          f[8 * j + 4] = bf_lo(v[i][j].z); f[8 * j + 5] = bf_hi(v[i][j].z); f[8 * j + 6] = bf_lo(v[i][j].w); f[8 * j + 7] = bf_hi(v[i][j].w);
        }
        float sum = 0.f;
#pragma unroll
        for (int j = 0; j < 32; j++) sum += f[j];
#pragma unroll
        for (int o = 16; o; o >>= 1) sum += __shfl_xor_sync(~0u, sum, o);
        const float mean = sum * (1.f / kD);
        TM(threadIdx.x == 256 && i == 0 && mean != 123.f, 57);
        float sq = 0.f;
#pragma unroll
        for (int j = 0; j < 32; j++) { const float dlt = f[j] - mean; sq = fmaf(dlt, dlt, sq); }
#pragma unroll
        for (int o = 16; o; o >>= 1) sq += __shfl_xor_sync(~0u, sq, o);
        const float mb = bf_round(mean);
        const float den = bf_round(sqrtf(bf_round(bf_round(sq * (1.f / kD)) + 1e-5f)));
        const float inv = 1.f / den;
        const int r = r0 + i;
        if (lane == 0) asm volatile("st.shared.v2.f32 [%0], {%1, %2};\n" ::"r"(statbuf + i * 8), "f"(mb), "f"(inv) : "memory");
#pragma unroll
        for (int j = 0; j < 4; j++) {
          uint4 o;
          uint32_t dd[4];
#pragma unroll
          for (int e = 0; e < 4; e++) {
            const uint32_t t = pack_bf16(f[8 * j + 2 * e] - mb, f[8 * j + 2 * e + 1] - mb);
            dd[e] = pack_bf16(bf_lo(t) * inv, bf_hi(t) * inv);
          }
          o.x = dd[0]; o.y = dd[1]; o.z = dd[2]; o.w = dd[3];
          const int ch = lane + 32 * j;
          asm volatile("st.shared.v4.b32 [%0], {%1, %2, %3, %4};\n" ::"r"(lnbuf + (ch >> 3) * 256 + i * 128 + (((ch & 7) ^ (r & 7)) << 4)),
                       "r"(o.x), "r"(o.y), "r"(o.z), "r"(o.w)
                       : "memory");
        }
      }
      TM(threadIdx.x == 256, 58);
      fence_async_smem();
      __syncwarp();
      if (lane < 17) {
        if (lane < 16) bulk_s2g(g_xn + ((size_t)(m * 16 + lane) * 128 + r0) * 128, lnbuf + lane * 256, 256);
        else bulk_s2g(g_stat + m * 128 + r0, statbuf, 16);
        bulk_commit();
        bulk_wait_all();
      }
      __syncwarp();
      if (lane == 0) flag_add(&g_flags[(F_XN + m) * 32], 1);
      TM(threadIdx.x == 256, 59);
    }
    cluster_wait();
    const int aw = (warp - 8) >> 2, w = warp & 3;
    const bool rel_lane = lane < 2;
    const uint32_t rel_addr = mapa(bars + B_KVEMPTY * 8, lane & 1);
    constexpr int NO = ONES ? 20 : 16;
    float s[32], o[NO];
    uint32_t p[16];
#pragma unroll
    for (int i = 0; i < 16; i++) p[i] = 0u;
#pragma unroll
    for (int i = 0; i < NO; i++) o[i] = 0.f;
#pragma unroll
    for (int i = 0; i < 32; i++) s[i] = 0.f;
    float l0 = 0.f, l1 = 0.f;
    const uint32_t hi64 = desc_hi(512, 2);
    const uint32_t kv_lo0 = desc_lo(sb + kKvOff, 16);
    uint32_t st = 0, ph = 0;
    uint32_t rel_cur = rel_addr;
    const uint32_t v_lo0 = desc_lo(sb + kKvOff + 4096, kOnesOff - kKvOff - 4096);
    auto issue_pv = [&](int acc) {
      const uint32_t v_lo = v_lo0 + st * (512u - (512u << 16));
      wgmma_rs_n40<1>(o, p[0], p[1], p[2], p[3], mk_desc(v_lo, hi64), acc);
      wgmma_rs_n40<1>(o, p[4], p[5], p[6], p[7], mk_desc(v_lo + (64u - (64u << 16)), hi64), 1);
      wgmma_rs_n40<1>(o, p[8], p[9], p[10], p[11], mk_desc(v_lo + (128u - (128u << 16)), hi64), 1);
      wgmma_rs_n40<1>(o, p[12], p[13], p[14], p[15], mk_desc(v_lo + (192u - (192u << 16)), hi64), 1);
    };
    auto issue_qk = [&](uint32_t q_lo) {
      const uint32_t k_lo = kv_lo0 + st * 512;
      wgmma_ss_n64<0>(s, mk_desc(q_lo, hi64), mk_desc(k_lo, hi64), 0);
      wgmma_ss_n64<0>(s, mk_desc(q_lo + 2, hi64), mk_desc(k_lo + 2, hi64), 1);
    };
    auto softmax_tile = [&]() {
#pragma unroll
      for (int i = 0; i < 8; i++) {
        const float e0 = ex2(s[4 * i]), e1 = ex2(s[4 * i + 1]), e2 = ex2(s[4 * i + 2]), e3 = ex2(s[4 * i + 3]);
        if (!ONES) { l0 += e0 + e1; l1 += e2 + e3; }
        p[2 * i] = pack_bf16(e0, e1); p[2 * i + 1] = pack_bf16(e2, e3);
      }
    };
    auto advance = [&]() {
      mbar_arrive_cluster_if(rel_cur, rel_lane);
      rel_cur += 8;
      if (++st == kNKv) { st = 0; ph ^= 1; rel_cur = rel_addr; }
    };
#pragma unroll 1
    for (int u = 0; u <= 4; u++) {
      const uint32_t q_lo = desc_lo(sb + kQOff + (u & 1) * 8192 + aw * 4096, 16);
      if (u < 4) mbar_wait(bars + (B_QFULL + (u & 1)) * 8, u >> 1);
      mbar_wait(bars + (B_KVFULL + st) * 8, ph);
      fence_regs(s); fence_regs(o); fence_regs(p);
      wgmma_fence();
      issue_pv(1);
      issue_qk(q_lo);
      wgmma_commit();
      wgmma_wait<0>();
      fence_regs(s); fence_regs(o); fence_regs(p);
      advance();
      if (u > 0) {
        const uint32_t ob = sb + kQOff + ((u - 1) & 1) * 8192 + aw * 4096;
        l0 = o[16]; l1 = o[18];
        bool ok = l0 >= 8.271806e-25f && l0 <= 1.2676506e30f && l1 >= 8.271806e-25f && l1 <= 1.2676506e30f;
#pragma unroll
        for (int i = 0; i < 16; i++) ok = ok && (fabsf(o[i]) <= 3.0e38f);
        const float i0 = 1.f / l0, i1 = 1.f / l1;
        uint32_t r[8];
#pragma unroll
        for (int i = 0; i < 4; i++) {
          r[2 * i] = pack_bf16(o[4 * i] * i0, o[4 * i + 1] * i0);
          r[2 * i + 1] = pack_bf16(o[4 * i + 2] * i1, o[4 * i + 3] * i1);
        }
        if (__any_sync(~0u, !ok)) {
          float e[16];
          attn_exact(e, ob + w * 1024, g_kv + (size_t)(8 * (u - 1) + c) * 32 * 8192);
#pragma unroll
          for (int i = 0; i < 8; i++) r[i] = pack_bf16(e[2 * i], e[2 * i + 1]);
        }
        __syncwarp();
        const uint32_t srow = w * 16 + (lane & 7) + ((lane >> 3) & 1) * 8, scol = lane >> 4;
        const uint32_t base = ob + srow * 64, sw = (srow >> 1) & 3;
        stsm4(base + ((scol ^ sw) << 4), r[0], r[1], r[2], r[3]);
        stsm4(base + (((2 + scol) ^ sw) << 4), r[4], r[5], r[6], r[7]);
        epi_publish(bars + (B_AST + aw * 2 + ((u - 1) & 1)) * 8, lane);
        l0 = 0.f; l1 = 0.f;
        TM(threadIdx.x == 256, 30 + u);
        TPUT(threadIdx.x == 256, 46 + u, clk32());
      }
      if (u == 4) break;
      bool ready = false;
      softmax_tile();
#pragma unroll 1
      for (int j = 1; j < 32; j++) {
        if (!EARLYW || !ready) mbar_wait(bars + (B_KVFULL + st) * 8, ph);
          fence_regs(s); fence_regs(o); fence_regs(p);
        wgmma_fence(); issue_pv(j != 1); issue_qk(q_lo); wgmma_commit(); wgmma_wait<0>();
        fence_regs(s); fence_regs(o); fence_regs(p);
        advance();
        if (EARLYW) ready = mbar_test(bars + (B_KVFULL + st) * 8, ph);
        softmax_tile();
      }
    }
  }

  cluster_arrive();
  cluster_wait();
  if (threadIdx.x == 0) {
    TM(true, 40);
    asm volatile("fence.acq_rel.gpu;\n" ::: "memory");
    const unsigned old = atomicAdd(&g_flags[F_DONE * 32], 1u);
    if (old == kCtas - 1) {
      asm volatile("fence.acq_rel.gpu;\n" ::: "memory");
      for (int i = 0; i < F_COUNT; i++) g_flags[i * 32] = 0u;
    }
  }
}

typedef CUresult (*EncodeFn)(CUtensorMap*, CUtensorMapDataType, cuuint32_t, void*, const cuuint64_t*, const cuuint64_t*,
                             const cuuint32_t*, const cuuint32_t*, CUtensorMapInterleave, CUtensorMapSwizzle,
                             CUtensorMapL2promotion, CUtensorMapFloatOOBfill);

void encode(EncodeFn fn, CUtensorMap* map, const void* base, int rank, const cuuint64_t* dims, const cuuint64_t* strides,
            const cuuint32_t* box, CUtensorMapSwizzle sw) {
  const cuuint32_t es[5] = {1, 1, 1, 1, 1};
  fn(map, CU_TENSOR_MAP_DATA_TYPE_BFLOAT16, rank, const_cast<void*>(base), dims, strides, box, es,
     CU_TENSOR_MAP_INTERLEAVE_NONE, sw, CU_TENSOR_MAP_L2_PROMOTION_L2_256B, CU_TENSOR_MAP_FLOAT_OOB_FILL_NONE);
}

}

extern "C" void kernel_launch(void* const* d_in, const int* in_sizes, int n_in, void* d_out, int out_size) {
  (void)in_sizes; (void)n_in; (void)out_size;
  static Params P;
  static const void* key[6] = {nullptr, nullptr, nullptr, nullptr, nullptr, nullptr};
  const void* cur[6] = {d_in[0], d_in[1], d_in[2], d_in[4], d_in[5], d_out};
  bool same = true;
  for (int i = 0; i < 6; i++) same = same && key[i] == cur[i];
  if (!same) {
    void* fn = nullptr;
    cudaDriverEntryPointQueryResult q;
    cudaGetDriverEntryPoint("cuTensorMapEncodeTiled", &fn, cudaEnableDefault, &q);
    EncodeFn enc = (EncodeFn)fn;
    {
      const cuuint64_t d[4] = {256, 1024, 4, 3}, s[3] = {6144, 512, 2048};
      const cuuint32_t b1[4] = {32, 32, 1, 3}, b2[4] = {32, 32, 2, 3};
      encode(enc, &P.wqkv1, d_in[1], 4, d, s, b1, CU_TENSOR_MAP_SWIZZLE_64B);
      encode(enc, &P.wqkv2, d_in[1], 4, d, s, b2, CU_TENSOR_MAP_SWIZZLE_64B);
    }
    {
      const cuuint64_t d[3] = {64, 1024, 56}, s[2] = {kDff * 2, 128};
      const cuuint32_t b3[3] = {64, 32, 3};
      encode(enc, &P.w1a, d_in[4], 3, d, s, b3, CU_TENSOR_MAP_SWIZZLE_128B);
      const cuuint64_t dc[3] = {32, 1024, 112}, sc[2] = {kDff * 2, 64};
      const cuuint32_t bc[3] = {32, 32, 2};
      encode(enc, &P.w1c, d_in[4], 3, dc, sc, bc, CU_TENSOR_MAP_SWIZZLE_64B);
    }
    {
      const cuuint64_t d2[3] = {64, kDff, 16}, d1[3] = {64, kD, 16}, s[2] = {kD * 2, 128};
      const cuuint32_t b[3] = {64, 32, 2};
      encode(enc, &P.w2, d_in[5], 3, d2, s, b, CU_TENSOR_MAP_SWIZZLE_128B);
      encode(enc, &P.wo, d_in[2], 3, d1, s, b, CU_TENSOR_MAP_SWIZZLE_128B);
    }
    {
      const cuuint64_t d[2] = {kD, kS}, s[1] = {kD * 2};
      const cuuint32_t bx[2] = {64, 128}, bo[2] = {64, 64};
      encode(enc, &P.x, d_in[0], 2, d, s, bx, CU_TENSOR_MAP_SWIZZLE_128B);
      encode(enc, &P.out, d_out, 2, d, s, bo, CU_TENSOR_MAP_SWIZZLE_128B);
    }
    P.xptr = (const __nv_bfloat16*)d_in[0];
    P.wqkv_p = (const uint8_t*)d_in[1];
    P.wo_p = (const uint8_t*)d_in[2];
    P.w1_p = (const uint8_t*)d_in[4];
    P.w2_p = (const uint8_t*)d_in[5];
    cudaFuncSetAttribute(fused_block_kernel, cudaFuncAttributeMaxDynamicSharedMemorySize, kSmemBytes);
    for (int i = 0; i < 6; i++) key[i] = cur[i];
  }
  fused_block_kernel<<<kCtas, kThreads, kSmemBytes>>>(P);
}
```

```cpp
#include <cuda_runtime.h>
#include <cuda_bf16.h>
#include <cuda.h>
#include <stdint.h>

#define GD192 1
#define GDOUT GD128
#define EVF 0
#define PFD 0
#define MAPV 2
#define PREF 0
#define ONES 1
#define EARLYW 1
#define GD128 1

namespace {

constexpr int kS = 2048, kD = 1024, kDff = 3584;
constexpr int kThreads = 512;
constexpr int kCtas = 128;

constexpr uint32_t kSlot = 40960;
constexpr uint32_t kStageOff = 3 * kSlot;
constexpr uint32_t kOutSlot = 2;
constexpr uint32_t kKvOff = 4 * kSlot + 8192;
constexpr uint32_t kNKv = 5;
constexpr uint32_t kQOff = kKvOff + kNKv * 8192;
constexpr uint32_t kBarOff = kQOff + 2 * 8192;
constexpr uint32_t kOnesOff = kBarOff + 512;
constexpr uint32_t kSmemBytes = kOnesOff + 1024 + 1024;
constexpr uint32_t B_GFULL = 0, B_GEMPTY = 4, B_KVFULL = 8, B_KVEMPTY = 13, B_QFULL = 18, B_QEMPTY = 20, B_GST = 22,
                   B_AST = 24, B_STAT = 28;

__device__ __align__(1024) uint8_t g_xn[16 * 16 * 16384];
__device__ __align__(1024) uint8_t g_q[32 * 2048 * 64];
__device__ __align__(1024) uint8_t g_kv[32 * 32 * 8192];
__device__ __align__(1024) uint8_t g_h[16 * 56 * 16384];
__device__ __align__(1024) uint8_t g_o[16 * 32 * 8192];
__device__ __align__(1024) float2 g_stat[2048];
constexpr int F_XN = 0, F_KV = 16, F_H = 48, F_O = 96, F_DONE = 160, F_COUNT = 161;
__device__ unsigned g_flags[F_COUNT * 32];

__device__ __forceinline__ uint32_t smem_u32(const void* p) { return (uint32_t)__cvta_generic_to_shared(p); }
__device__ __forceinline__ void wgmma_fence() { asm volatile("wgmma.fence.sync.aligned;\n" ::: "memory"); }
__device__ __forceinline__ void wgmma_commit() { asm volatile("wgmma.commit_group.sync.aligned;\n" ::: "memory"); }
template <int N>
__device__ __forceinline__ void wgmma_wait() { asm volatile("wgmma.wait_group.sync.aligned %0;\n" ::"n"(N) : "memory"); }
template <int N>
__device__ __forceinline__ void fence_regs(float (&r)[N]) {
#pragma unroll
  for (int i = 0; i < N; i++) asm volatile("" : "+f"(r[i])::"memory");
}
template <int N>
__device__ __forceinline__ void fence_regs(uint32_t (&r)[N]) {
#pragma unroll
  for (int i = 0; i < N; i++) asm volatile("" : "+r"(r[i])::"memory");
}
__device__ __forceinline__ uint64_t mk_desc(uint32_t lo, uint32_t hi) { return ((uint64_t)hi << 32) | lo; }
__host__ __device__ constexpr uint32_t desc_hi(uint32_t sbo, uint32_t swz) { return (sbo >> 4) | (swz << 30); }
__device__ __forceinline__ uint32_t desc_lo(uint32_t addr, uint32_t lbo) { return ((addr & 0x3FFFF) >> 4) | ((lbo >> 4) << 16); }

__device__ __forceinline__ void mbar_init(uint32_t bar, uint32_t cnt) {
  asm volatile("mbarrier.init.shared::cta.b64 [%0], %1;\n" ::"r"(bar), "r"(cnt) : "memory");
}
__device__ __forceinline__ void mbar_expect_tx(uint32_t bar, uint32_t bytes) {
  asm volatile("mbarrier.arrive.expect_tx.shared::cta.b64 _, [%0], %1;\n" ::"r"(bar), "r"(bytes) : "memory");
}
__device__ __forceinline__ void mbar_arrive(uint32_t bar) {
  asm volatile("mbarrier.arrive.shared::cta.b64 _, [%0];\n" ::"r"(bar) : "memory");
}
__device__ __forceinline__ void mbar_arrive_cta(uint32_t bar, uint32_t cta, uint32_t cnt) {
  asm volatile(
      "{\n.reg .b32 ra;\nmapa.shared::cluster.u32 ra, %0, %1;\nmbarrier.arrive.shared::cluster.b64 _, [ra], %2;\n}\n" ::"r"(bar),
      "r"(cta), "r"(cnt)
      : "memory");
}
__device__ __forceinline__ bool mbar_test(uint32_t bar, uint32_t parity) {
  uint32_t ok;
  asm volatile("{\n.reg .pred p;\nmbarrier.test_wait.parity.shared::cta.b64 p, [%1], %2;\nselp.u32 %0, 1, 0, p;\n}\n"
               : "=r"(ok)
               : "r"(bar), "r"(parity)
               : "memory");
  return ok;
}
__device__ __forceinline__ void mbar_wait(uint32_t bar, uint32_t parity) {
  asm volatile(
      "{\n.reg .pred p, q;\n.reg .u32 it;\nmov.u32 it, 0;\n"
      "LW_%=:\n"
      "mbarrier.try_wait.parity.shared::cta.b64 p, [%0], %1;\n"
      "@p bra LD_%=;\n"
      "add.u32 it, it, 1;\n"
      "setp.lt.u32 q, it, 0x400000;\n"
      "@q bra LW_%=;\n"
      "trap;\n"
      "LD_%=:\n}\n" ::"r"(bar), "r"(parity) : "memory");
}
__device__ __forceinline__ void mbar_wait_sleepy(uint32_t bar, uint32_t parity) {
  asm volatile(
      "{\n.reg .pred p, q;\n.reg .u32 it;\nmov.u32 it, 0;\n"
      "LW_%=:\n"
      "mbarrier.try_wait.parity.shared::cta.b64 p, [%0], %1, 20000;\n"
      "@p bra LD_%=;\n"
      "add.u32 it, it, 1;\n"
      "setp.lt.u32 q, it, 0x400000;\n"
      "@q bra LW_%=;\n"
      "trap;\n"
      "LD_%=:\n}\n" ::"r"(bar), "r"(parity) : "memory");
}
__device__ __forceinline__ uint32_t mapa(uint32_t addr, uint32_t cta) {
  uint32_t r;
  asm("mapa.shared::cluster.u32 %0, %1, %2;\n" : "=r"(r) : "r"(addr), "r"(cta));
  return r;
}
__device__ __forceinline__ void mbar_arrive_cluster_if(uint32_t addr, bool pred) {
  asm volatile("{\n.reg .pred p;\nsetp.ne.u32 p, %1, 0;\n@p mbarrier.arrive.shared::cluster.b64 _, [%0];\n}\n" ::"r"(addr),
               "r"((uint32_t)pred)
               : "memory");
}
__device__ __forceinline__ void flag_wait(const unsigned* f, unsigned target) {
  uint32_t it = 0;
#pragma unroll 1
  while (true) {
    unsigned v;
    asm volatile("ld.acquire.gpu.global.u32 %0, [%1];\n" : "=r"(v) : "l"(f) : "memory");
    if (v >= target) break;
    if (++it > (1u << 22)) asm volatile("trap;");
  }
  asm volatile("fence.proxy.async.global;\n" ::: "memory");
}
__device__ __forceinline__ void flag_add(unsigned* f, unsigned v) {
  asm volatile("red.relaxed.gpu.global.add.u32 [%0], %1;\n" ::"l"(f), "r"(v) : "memory");
}
__device__ __forceinline__ bool elect_one() {
  uint32_t p;
  asm volatile("{\n.reg .pred P;\nelect.sync _|P, 0xffffffff;\nselp.u32 %0, 1, 0, P;\n}\n" : "=r"(p));
  return p;
}
__device__ __forceinline__ void bulk_g2s(uint32_t dst, const void* src, uint32_t bytes, uint32_t bar) {
  asm volatile("cp.async.bulk.shared::cluster.global.mbarrier::complete_tx::bytes [%0], [%1], %2, [%3];\n" ::"r"(dst),
               "l"(src), "r"(bytes), "r"(bar)
               : "memory");
}
__device__ __forceinline__ void bulk_g2s_mc(uint32_t dst, const void* src, uint32_t bytes, uint32_t bar) {
  asm volatile(
      "cp.async.bulk.shared::cluster.global.mbarrier::complete_tx::bytes.multicast::cluster [%0], [%1], %2, [%3], %4;\n" ::"r"(dst),
      "l"(src), "r"(bytes), "r"(bar), "h"((uint16_t)3)
      : "memory");
}
__device__ __forceinline__ void bulk_s2g(void* dst, uint32_t src, uint32_t bytes) {
  asm volatile("cp.async.bulk.global.shared::cta.bulk_group [%0], [%1], %2;\n" ::"l"(dst), "r"(src), "r"(bytes) : "memory");
}
__device__ __forceinline__ void l2_prefetch(const void* src, uint32_t bytes) {
  asm volatile("cp.async.bulk.prefetch.L2.global [%0], %1;\n" ::"l"(src), "r"(bytes) : "memory");
}
__device__ __forceinline__ void bulk_commit() { asm volatile("cp.async.bulk.commit_group;\n" ::: "memory"); }
__device__ __forceinline__ void bulk_wait_read() { asm volatile("cp.async.bulk.wait_group.read 0;\n" ::: "memory"); }
__device__ __forceinline__ void bulk_wait_all() { asm volatile("cp.async.bulk.wait_group 0;\n" ::: "memory"); }
__device__ __forceinline__ void tma_2d(uint32_t dst, const CUtensorMap* m, int c0, int c1, uint32_t bar) {
  asm volatile(
      "cp.async.bulk.tensor.2d.shared::cluster.global.mbarrier::complete_tx::bytes [%0], [%1, {%3, %4}], [%2];\n" ::"r"(dst),
      "l"((uint64_t)m), "r"(bar), "r"(c0), "r"(c1)
      : "memory");
}
__device__ __forceinline__ uint64_t policy_evict_first() {
  uint64_t p;
  asm volatile("createpolicy.fractional.L2::evict_first.b64 %0, 1.0;\n" : "=l"(p));
  return p;
}
__device__ __forceinline__ void tma_3d_mc(uint32_t dst, const CUtensorMap* m, int c0, int c1, int c2, uint32_t bar, uint64_t pol) {
  asm volatile(
      "cp.async.bulk.tensor.3d.shared::cluster.global.mbarrier::complete_tx::bytes.multicast::cluster [%0], [%1, {%3, %4, %5}], "
      "[%2], %6;\n" ::"r"(dst),
      "l"((uint64_t)m), "r"(bar), "r"(c0), "r"(c1), "r"(c2), "h"((uint16_t)3)
      : "memory");
}
__device__ __forceinline__ void tma_4d_mc(uint32_t dst, const CUtensorMap* m, int c0, int c1, int c2, int c3, uint32_t bar, uint64_t pol) {
  asm volatile(
      "cp.async.bulk.tensor.4d.shared::cluster.global.mbarrier::complete_tx::bytes.multicast::cluster [%0], [%1, {%3, %4, %5, "
      "%6}], [%2], %7;\n" ::"r"(dst),
      "l"((uint64_t)m), "r"(bar), "r"(c0), "r"(c1), "r"(c2), "r"(c3), "h"((uint16_t)3)
      : "memory");
}
__device__ __forceinline__ void tma_pf_3d(const CUtensorMap* m, int c0, int c1, int c2) {
  asm volatile("cp.async.bulk.prefetch.tensor.3d.L2.global [%0, {%1, %2, %3}];\n" ::"l"((uint64_t)m), "r"(c0), "r"(c1), "r"(c2) : "memory");
}
__device__ __forceinline__ void tma_pf_4d(const CUtensorMap* m, int c0, int c1, int c2, int c3) {
  asm volatile("cp.async.bulk.prefetch.tensor.4d.L2.global [%0, {%1, %2, %3, %4}];\n" ::"l"((uint64_t)m), "r"(c0), "r"(c1), "r"(c2),
               "r"(c3)
               : "memory");
}
__device__ __forceinline__ void tma_store_2d(const CUtensorMap* m, uint32_t src, int c0, int c1) {
  asm volatile("cp.async.bulk.tensor.2d.global.shared::cta.bulk_group [%0, {%2, %3}], [%1];\n" ::"l"((uint64_t)m), "r"(src),
               "r"(c0), "r"(c1)
               : "memory");
}
__device__ __forceinline__ void prefetch_map(const CUtensorMap* m) {
  asm volatile("prefetch.tensormap [%0];\n" ::"l"((uint64_t)m) : "memory");
}
__device__ __forceinline__ void fence_async_smem() { asm volatile("fence.proxy.async.shared::cta;\n" ::: "memory"); }
__device__ __forceinline__ void stsm4(uint32_t addr, uint32_t a, uint32_t b, uint32_t c, uint32_t d) {
  asm volatile("stmatrix.sync.aligned.m8n8.x4.shared.b16 [%0], {%1, %2, %3, %4};\n" ::"r"(addr), "r"(a), "r"(b), "r"(c), "r"(d)
               : "memory");
}
__device__ __forceinline__ void ldsm4(uint32_t addr, uint32_t& a, uint32_t& b, uint32_t& c, uint32_t& d) {
  asm volatile("ldmatrix.sync.aligned.m8n8.x4.shared.b16 {%0, %1, %2, %3}, [%4];\n"
               : "=r"(a), "=r"(b), "=r"(c), "=r"(d)
               : "r"(addr)
               : "memory");
}
__device__ __forceinline__ float ex2(float x) {
  float y;
  asm("ex2.approx.ftz.f32 %0, %1;" : "=f"(y) : "f"(x));
  return y;
}
__device__ __forceinline__ uint32_t pack_bf16(float lo, float hi) {
  uint32_t r;
  asm("cvt.rn.bf16x2.f32 %0, %1, %2;" : "=r"(r) : "f"(hi), "f"(lo));
  return r;
}
__device__ __forceinline__ uint32_t pack_bf16_relu(float lo, float hi) {
  uint32_t r;
  asm("cvt.rn.relu.bf16x2.f32 %0, %1, %2;" : "=r"(r) : "f"(hi), "f"(lo));
  return r;
}
__device__ __forceinline__ float bf_lo(uint32_t v) { return __uint_as_float(v << 16); }
__device__ __forceinline__ float bf_hi(uint32_t v) { return __uint_as_float(v & 0xffff0000u); }
__device__ __forceinline__ float bf_round(float x) { return __bfloat162float(__float2bfloat16_rn(x)); }
__device__ __forceinline__ void named_sync(int id) { asm volatile("bar.sync %0, 128;\n" ::"r"(id) : "memory"); }
__device__ __forceinline__ void cluster_arrive() { asm volatile("barrier.cluster.arrive.relaxed.aligned;\n" ::: "memory"); }
__device__ __forceinline__ void cluster_wait() { asm volatile("barrier.cluster.wait.acquire.aligned;\n" ::: "memory"); }
#define TM(cond, idx)
#define TACC(acc, stmt) do { stmt; } while (0)
#define TPUT(cond, idx, v)

template <int TB>
__device__ __forceinline__ void wgmma_ss_n192(float (&d)[96], uint64_t da, uint64_t db, int scale_d) {
  asm volatile(
      "{\n.reg .pred p;\nsetp.ne.b32 p, %98, 0;\n"
      "wgmma.mma_async.sync.aligned.m64n192k16.f32.bf16.bf16 {"
      "%0, %1, %2, %3, %4, %5, %6, %7, %8, %9, %10, %11, %12, %13, %14, %15, "
      "%16, %17, %18, %19, %20, %21, %22, %23, %24, %25, %26, %27, %28, %29, %30, %31, "
      "%32, %33, %34, %35, %36, %37, %38, %39, %40, %41, %42, %43, %44, %45, %46, %47, "
      "%48, %49, %50, %51, %52, %53, %54, %55, %56, %57, %58, %59, %60, %61, %62, %63, "
      "%64, %65, %66, %67, %68, %69, %70, %71, %72, %73, %74, %75, %76, %77, %78, %79, "
      "%80, %81, %82, %83, %84, %85, %86, %87, %88, %89, %90, %91, %92, %93, %94, %95}, %96, %97, p, 1, 1, 0, %99;\n}\n"
      : "+f"(d[0]), "+f"(d[1]), "+f"(d[2]), "+f"(d[3]), "+f"(d[4]), "+f"(d[5]), "+f"(d[6]), "+f"(d[7]),
        "+f"(d[8]), "+f"(d[9]), "+f"(d[10]), "+f"(d[11]), "+f"(d[12]), "+f"(d[13]), "+f"(d[14]), "+f"(d[15]),
        "+f"(d[16]), "+f"(d[17]), "+f"(d[18]), "+f"(d[19]), "+f"(d[20]), "+f"(d[21]), "+f"(d[22]), "+f"(d[23]),
        "+f"(d[24]), "+f"(d[25]), "+f"(d[26]), "+f"(d[27]), "+f"(d[28]), "+f"(d[29]), "+f"(d[30]), "+f"(d[31]),
        "+f"(d[32]), "+f"(d[33]), "+f"(d[34]), "+f"(d[35]), "+f"(d[36]), "+f"(d[37]), "+f"(d[38]), "+f"(d[39]),
        "+f"(d[40]), "+f"(d[41]), "+f"(d[42]), "+f"(d[43]), "+f"(d[44]), "+f"(d[45]), "+f"(d[46]), "+f"(d[47]),
        "+f"(d[48]), "+f"(d[49]), "+f"(d[50]), "+f"(d[51]), "+f"(d[52]), "+f"(d[53]), "+f"(d[54]), "+f"(d[55]),
        "+f"(d[56]), "+f"(d[57]), "+f"(d[58]), "+f"(d[59]), "+f"(d[60]), "+f"(d[61]), "+f"(d[62]), "+f"(d[63]),
        "+f"(d[64]), "+f"(d[65]), "+f"(d[66]), "+f"(d[67]), "+f"(d[68]), "+f"(d[69]), "+f"(d[70]), "+f"(d[71]),
        "+f"(d[72]), "+f"(d[73]), "+f"(d[74]), "+f"(d[75]), "+f"(d[76]), "+f"(d[77]), "+f"(d[78]), "+f"(d[79]),
        "+f"(d[80]), "+f"(d[81]), "+f"(d[82]), "+f"(d[83]), "+f"(d[84]), "+f"(d[85]), "+f"(d[86]), "+f"(d[87]),
        "+f"(d[88]), "+f"(d[89]), "+f"(d[90]), "+f"(d[91]), "+f"(d[92]), "+f"(d[93]), "+f"(d[94]), "+f"(d[95])
      : "l"(da), "l"(db), "r"(scale_d), "n"(TB));
}
template <int TB>
__device__ __forceinline__ void wgmma_ss_n160(float (&d)[96], uint64_t da, uint64_t db, int scale_d) {
  asm volatile(
      "{\n.reg .pred p;\nsetp.ne.b32 p, %82, 0;\n"
      "wgmma.mma_async.sync.aligned.m64n160k16.f32.bf16.bf16 {"
      "%0, %1, %2, %3, %4, %5, %6, %7, %8, %9, %10, %11, %12, %13, %14, %15, "
      "%16, %17, %18, %19, %20, %21, %22, %23, %24, %25, %26, %27, %28, %29, %30, %31, "
      "%32, %33, %34, %35, %36, %37, %38, %39, %40, %41, %42, %43, %44, %45, %46, %47, "
      "%48, %49, %50, %51, %52, %53, %54, %55, %56, %57, %58, %59, %60, %61, %62, %63, "
      "%64, %65, %66, %67, %68, %69, %70, %71, %72, %73, %74, %75, %76, %77, %78, %79}, %80, %81, p, 1, 1, 0, %83;\n}\n"
      : "+f"(d[0]), "+f"(d[1]), "+f"(d[2]), "+f"(d[3]), "+f"(d[4]), "+f"(d[5]), "+f"(d[6]), "+f"(d[7]),
        "+f"(d[8]), "+f"(d[9]), "+f"(d[10]), "+f"(d[11]), "+f"(d[12]), "+f"(d[13]), "+f"(d[14]), "+f"(d[15]),
        "+f"(d[16]), "+f"(d[17]), "+f"(d[18]), "+f"(d[19]), "+f"(d[20]), "+f"(d[21]), "+f"(d[22]), "+f"(d[23]),
        "+f"(d[24]), "+f"(d[25]), "+f"(d[26]), "+f"(d[27]), "+f"(d[28]), "+f"(d[29]), "+f"(d[30]), "+f"(d[31]),
        "+f"(d[32]), "+f"(d[33]), "+f"(d[34]), "+f"(d[35]), "+f"(d[36]), "+f"(d[37]), "+f"(d[38]), "+f"(d[39]),
        "+f"(d[40]), "+f"(d[41]), "+f"(d[42]), "+f"(d[43]), "+f"(d[44]), "+f"(d[45]), "+f"(d[46]), "+f"(d[47]),
        "+f"(d[48]), "+f"(d[49]), "+f"(d[50]), "+f"(d[51]), "+f"(d[52]), "+f"(d[53]), "+f"(d[54]), "+f"(d[55]),
        "+f"(d[56]), "+f"(d[57]), "+f"(d[58]), "+f"(d[59]), "+f"(d[60]), "+f"(d[61]), "+f"(d[62]), "+f"(d[63]),
        "+f"(d[64]), "+f"(d[65]), "+f"(d[66]), "+f"(d[67]), "+f"(d[68]), "+f"(d[69]), "+f"(d[70]), "+f"(d[71]),
        "+f"(d[72]), "+f"(d[73]), "+f"(d[74]), "+f"(d[75]), "+f"(d[76]), "+f"(d[77]), "+f"(d[78]), "+f"(d[79])
      : "l"(da), "l"(db), "r"(scale_d), "n"(TB));
}
template <int TB>
__device__ __forceinline__ void wgmma_ss_n128(float (&d)[96], uint64_t da, uint64_t db, int scale_d) {
  asm volatile(
      "{\n.reg .pred p;\nsetp.ne.b32 p, %66, 0;\n"
      "wgmma.mma_async.sync.aligned.m64n128k16.f32.bf16.bf16 {"
      "%0, %1, %2, %3, %4, %5, %6, %7, %8, %9, %10, %11, %12, %13, %14, %15, "
      "%16, %17, %18, %19, %20, %21, %22, %23, %24, %25, %26, %27, %28, %29, %30, %31, "
      "%32, %33, %34, %35, %36, %37, %38, %39, %40, %41, %42, %43, %44, %45, %46, %47, "
      "%48, %49, %50, %51, %52, %53, %54, %55, %56, %57, %58, %59, %60, %61, %62, %63}, %64, %65, p, 1, 1, 0, %67;\n}\n"
      : "+f"(d[0]), "+f"(d[1]), "+f"(d[2]), "+f"(d[3]), "+f"(d[4]), "+f"(d[5]), "+f"(d[6]), "+f"(d[7]),
        "+f"(d[8]), "+f"(d[9]), "+f"(d[10]), "+f"(d[11]), "+f"(d[12]), "+f"(d[13]), "+f"(d[14]), "+f"(d[15]),
        "+f"(d[16]), "+f"(d[17]), "+f"(d[18]), "+f"(d[19]), "+f"(d[20]), "+f"(d[21]), "+f"(d[22]), "+f"(d[23]),
        "+f"(d[24]), "+f"(d[25]), "+f"(d[26]), "+f"(d[27]), "+f"(d[28]), "+f"(d[29]), "+f"(d[30]), "+f"(d[31]),
        "+f"(d[32]), "+f"(d[33]), "+f"(d[34]), "+f"(d[35]), "+f"(d[36]), "+f"(d[37]), "+f"(d[38]), "+f"(d[39]),
        "+f"(d[40]), "+f"(d[41]), "+f"(d[42]), "+f"(d[43]), "+f"(d[44]), "+f"(d[45]), "+f"(d[46]), "+f"(d[47]),
        "+f"(d[48]), "+f"(d[49]), "+f"(d[50]), "+f"(d[51]), "+f"(d[52]), "+f"(d[53]), "+f"(d[54]), "+f"(d[55]),
        "+f"(d[56]), "+f"(d[57]), "+f"(d[58]), "+f"(d[59]), "+f"(d[60]), "+f"(d[61]), "+f"(d[62]), "+f"(d[63])
      : "l"(da), "l"(db), "r"(scale_d), "n"(TB));
}
template <int TB>
__device__ __forceinline__ void wgmma_ss_n96(float (&d)[96], uint64_t da, uint64_t db, int scale_d) {
  asm volatile(
      "{\n.reg .pred p;\nsetp.ne.b32 p, %50, 0;\n"
      "wgmma.mma_async.sync.aligned.m64n96k16.f32.bf16.bf16 {"
      "%0, %1, %2, %3, %4, %5, %6, %7, %8, %9, %10, %11, %12, %13, %14, %15, "
      "%16, %17, %18, %19, %20, %21, %22, %23, %24, %25, %26, %27, %28, %29, %30, %31, "
      "%32, %33, %34, %35, %36, %37, %38, %39, %40, %41, %42, %43, %44, %45, %46, %47}, %48, %49, p, 1, 1, 0, %51;\n}\n"
      : "+f"(d[0]), "+f"(d[1]), "+f"(d[2]), "+f"(d[3]), "+f"(d[4]), "+f"(d[5]), "+f"(d[6]), "+f"(d[7]),
        "+f"(d[8]), "+f"(d[9]), "+f"(d[10]), "+f"(d[11]), "+f"(d[12]), "+f"(d[13]), "+f"(d[14]), "+f"(d[15]),
        "+f"(d[16]), "+f"(d[17]), "+f"(d[18]), "+f"(d[19]), "+f"(d[20]), "+f"(d[21]), "+f"(d[22]), "+f"(d[23]),
        "+f"(d[24]), "+f"(d[25]), "+f"(d[26]), "+f"(d[27]), "+f"(d[28]), "+f"(d[29]), "+f"(d[30]), "+f"(d[31]),
        "+f"(d[32]), "+f"(d[33]), "+f"(d[34]), "+f"(d[35]), "+f"(d[36]), "+f"(d[37]), "+f"(d[38]), "+f"(d[39]),
        "+f"(d[40]), "+f"(d[41]), "+f"(d[42]), "+f"(d[43]), "+f"(d[44]), "+f"(d[45]), "+f"(d[46]), "+f"(d[47])
      : "l"(da), "l"(db), "r"(scale_d), "n"(TB));
}
template <int TB>
__device__ __forceinline__ void wgmma_ss_n64(float (&d)[32], uint64_t da, uint64_t db, int scale_d) {
  asm volatile(
      "{\n.reg .pred p;\nsetp.ne.b32 p, %34, 0;\n"
      "wgmma.mma_async.sync.aligned.m64n64k16.f32.bf16.bf16 {"
      "%0, %1, %2, %3, %4, %5, %6, %7, %8, %9, %10, %11, %12, %13, %14, %15, "
      "%16, %17, %18, %19, %20, %21, %22, %23, %24, %25, %26, %27, %28, %29, %30, %31}, %32, %33, p, 1, 1, 0, %35;\n}\n"
      : "+f"(d[0]), "+f"(d[1]), "+f"(d[2]), "+f"(d[3]), "+f"(d[4]), "+f"(d[5]), "+f"(d[6]), "+f"(d[7]),
        "+f"(d[8]), "+f"(d[9]), "+f"(d[10]), "+f"(d[11]), "+f"(d[12]), "+f"(d[13]), "+f"(d[14]), "+f"(d[15]),
        "+f"(d[16]), "+f"(d[17]), "+f"(d[18]), "+f"(d[19]), "+f"(d[20]), "+f"(d[21]), "+f"(d[22]), "+f"(d[23]),
        "+f"(d[24]), "+f"(d[25]), "+f"(d[26]), "+f"(d[27]), "+f"(d[28]), "+f"(d[29]), "+f"(d[30]), "+f"(d[31])
      : "l"(da), "l"(db), "r"(scale_d), "n"(TB));
}
template <int TB>
__device__ __forceinline__ void wgmma_rs_n32(float (&d)[16], uint32_t a0, uint32_t a1, uint32_t a2, uint32_t a3,
                                             uint64_t db, int scale_d) {
  asm volatile(
      "{\n.reg .pred p;\nsetp.ne.b32 p, %21, 0;\n"
      "wgmma.mma_async.sync.aligned.m64n32k16.f32.bf16.bf16 {"
      "%0, %1, %2, %3, %4, %5, %6, %7, %8, %9, %10, %11, %12, %13, %14, %15}, {%16, %17, %18, %19}, %20, p, 1, 1, %22;\n}\n"
      : "+f"(d[0]), "+f"(d[1]), "+f"(d[2]), "+f"(d[3]), "+f"(d[4]), "+f"(d[5]), "+f"(d[6]), "+f"(d[7]),
        "+f"(d[8]), "+f"(d[9]), "+f"(d[10]), "+f"(d[11]), "+f"(d[12]), "+f"(d[13]), "+f"(d[14]), "+f"(d[15])
      : "r"(a0), "r"(a1), "r"(a2), "r"(a3), "l"(db), "r"(scale_d), "n"(TB));
}
template <int TB>
__device__ __forceinline__ void wgmma_rs_n40(float (&d)[20], uint32_t a0, uint32_t a1, uint32_t a2, uint32_t a3,
                                             uint64_t db, int scale_d) {
  asm volatile(
      "{\n.reg .pred p;\nsetp.ne.b32 p, %25, 0;\n"
      "wgmma.mma_async.sync.aligned.m64n40k16.f32.bf16.bf16 {"
      "%0, %1, %2, %3, %4, %5, %6, %7, %8, %9, %10, %11, %12, %13, %14, %15, "
      "%16, %17, %18, %19}, {%20, %21, %22, %23}, %24, p, 1, 1, %26;\n}\n"
      : "+f"(d[0]), "+f"(d[1]), "+f"(d[2]), "+f"(d[3]), "+f"(d[4]), "+f"(d[5]), "+f"(d[6]), "+f"(d[7]),
        "+f"(d[8]), "+f"(d[9]), "+f"(d[10]), "+f"(d[11]), "+f"(d[12]), "+f"(d[13]), "+f"(d[14]), "+f"(d[15]),
        "+f"(d[16]), "+f"(d[17]), "+f"(d[18]), "+f"(d[19])
      : "r"(a0), "r"(a1), "r"(a2), "r"(a3), "l"(db), "r"(scale_d), "n"(TB));
}

template <int N>
__device__ __forceinline__ void wgmma_gemm(float (&d)[96], uint64_t da, uint64_t db, int sc) {
  if constexpr (N == 192) wgmma_ss_n192<1>(d, da, db, sc);
  else if constexpr (N == 160) wgmma_ss_n160<1>(d, da, db, sc);
  else if constexpr (N == 128) wgmma_ss_n128<1>(d, da, db, sc);
  else wgmma_ss_n96<1>(d, da, db, sc);
}

__device__ __forceinline__ uint32_t next_slot(int pos, bool first_tile, uint32_t& r3) {
  const bool x = (pos & 3) == 3 && (first_tile || pos >= 7);
  const uint32_t s = x ? 3u : r3;
  r3 = x ? r3 : ((r3 == 2) ? 0u : r3 + 1);
  return s;
}
__device__ __forceinline__ bool out_kb_is_attn(int kb) { return (kb >= 32 && kb < 40) || kb >= 64; }

#define GWAIT(bar, par) do { if (!ready) mbar_wait(bar, par); } while (0)
template <int N, int NKB, int GD, bool OUTK>
__device__ __forceinline__ void gemm_mainloop(float (&d0)[96], float (&d1)[96], uint32_t lo0, uint32_t bars, uint32_t& phases,
                                              uint32_t& r3, uint32_t b_lbo, uint32_t b_hi, uint32_t b_k1, uint32_t b_k2,
                                              uint32_t rel_addr, bool rel_lane, uint32_t& twait) {
  const uint32_t a_c = lo0 + (1u << 16), b_c = lo0 + (16384 >> 4) + ((b_lbo >> 4) << 16);
  uint32_t s = next_slot(0, false, r3), rel = 0;
  uint32_t a_lo = a_c + s * (kSlot >> 4), b_lo = b_c + s * (kSlot >> 4);
  uint32_t a_hi = desc_hi(1024, 1), a_half = 8192 >> 4, a_k2 = 64 >> 4;
  bool ready = false, do_rel = false;
#pragma unroll 1
  for (int kb = 0; kb < NKB; kb++) {
    GWAIT(bars + (B_GFULL + s) * 8, (phases >> s) & 1);
    const uint32_t ca_lo = a_lo, cb_lo = b_lo, ca_hi = a_hi, ca_half = a_half, ca_k2 = a_k2;
    wgmma_fence();
#pragma unroll
    for (int k = 0; k < 4; k++) {
      const uint64_t db = mk_desc(cb_lo + (k >> 1) * b_k2 + (k & 1) * b_k1, b_hi);
      const uint32_t ak = ca_lo + (k >> 1) * ca_k2 + (k & 1) * 2;
      const int sc = (k > 0) ? 1 : (kb > 0);
      wgmma_wait<GD>();
      wgmma_gemm<N>(d0, mk_desc(ak, ca_hi), db, sc);
      wgmma_commit();
      if (2 * k == GD) mbar_arrive_cluster_if(rel, do_rel);
      wgmma_wait<GD>();
      wgmma_gemm<N>(d1, mk_desc(ak + ca_half, ca_hi), db, sc);
      wgmma_commit();
      if (2 * k + 1 == GD) mbar_arrive_cluster_if(rel, do_rel);
      if (k == 2) {
        phases ^= 1u << s;
        rel = rel_addr + s * 8;
        do_rel = rel_lane;
        uint32_t r3n = r3;
        const uint32_t sn = next_slot(kb + 1, false, r3n);
        if (kb + 1 < NKB) { s = sn; r3 = r3n; }
        a_lo = a_c + s * (kSlot >> 4);
        b_lo = b_c + s * (kSlot >> 4);
        if (OUTK) {
          const bool at = out_kb_is_attn(kb + 1);
          a_hi = at ? desc_hi(512, 2) : desc_hi(1024, 1);
          a_half = at ? 4096 >> 4 : 8192 >> 4;
          a_k2 = at ? 8192 >> 4 : 64 >> 4;
        }
        ready = mbar_test(bars + (B_GFULL + s) * 8, (phases >> s) & 1);
      }
    }
  }
  wgmma_wait<0>();
  fence_regs(d0);
  fence_regs(d1);
}

__device__ __forceinline__ void gemm_first(float (&d0)[96], float (&d1)[96], float (&cs)[3], uint32_t sb, uint32_t bars,
                                           uint32_t rank, uint32_t rel_addr, bool rel_lane, uint32_t& twait) {
  const int lane = threadIdx.x & 31, w = (threadIdx.x >> 5) & 3;
  const uint32_t a_lo0 = desc_lo(sb, 16), b_lo0 = desc_lo(sb + 16384, 2048);
  bool ready = false;
#pragma unroll 1
  for (int kb = 0; kb < 16; kb++) {
    const uint32_t s = kb & 3;
    GWAIT(bars + (B_GFULL + s) * 8, (kb >> 2) & 1);
    const uint32_t a_lo = a_lo0 + s * (kSlot >> 4), b_lo = b_lo0 + s * (kSlot >> 4);
    uint32_t bq[3][4];
#pragma unroll
    for (int i = 0; i < 3; i++) {
      const int nb = 3 * w + i;
      asm volatile("ldmatrix.sync.aligned.m8n8.x4.trans.shared.b16 {%0, %1, %2, %3}, [%4];\n"
                   : "=r"(bq[i][0]), "=r"(bq[i][1]), "=r"(bq[i][2]), "=r"(bq[i][3])
                   : "r"(sb + s * kSlot + 16384 + rank * 6144 + (nb >> 2) * 2048 + lane * 64 + (((nb & 3) ^ ((lane >> 1) & 3)) << 4)));
    }
    wgmma_fence();
#pragma unroll
    for (int k = 0; k < 4; k++) {
      const uint64_t db = mk_desc(b_lo + (k >> 1) * (6144 >> 4) + (k & 1) * (1024 >> 4), desc_hi(512, 2));
      const int sc = (k > 0) ? 1 : (kb > 0);
      wgmma_ss_n96<1>(d0, mk_desc(a_lo + 2 * k, desc_hi(1024, 1)), db, sc);
      wgmma_ss_n96<1>(d1, mk_desc(a_lo + 2 * k + (8192 >> 4), desc_hi(1024, 1)), db, sc);
    }
    wgmma_commit();
    wgmma_wait<1>();
    mbar_arrive_cluster_if(rel_addr + ((s + 3) & 3) * 8, rel_lane && kb > 0);
#pragma unroll
    for (int i = 0; i < 3; i++)
      cs[i] += ((bf_lo(bq[i][0]) + bf_hi(bq[i][0])) + (bf_lo(bq[i][1]) + bf_hi(bq[i][1]))) +
               ((bf_lo(bq[i][2]) + bf_hi(bq[i][2])) + (bf_lo(bq[i][3]) + bf_hi(bq[i][3])));
    asm volatile("" : "+f"(cs[0]), "+f"(cs[1]), "+f"(cs[2])::"memory");
    ready = mbar_test(bars + (B_GFULL + ((s + 1) & 3)) * 8, ((kb + 1) >> 2) & 1);
  }
  wgmma_wait<0>();
  fence_regs(d0);
  fence_regs(d1);
}

__device__ __forceinline__ void epi_publish(uint32_t bar, int lane) {
  fence_async_smem();
  __syncwarp();
  if (lane == 0) mbar_arrive(bar);
}
constexpr float kQScale = 0.17677669529663687f * 1.4426950408889634f;
template <int NJ, int NQ>
__device__ __forceinline__ void epi_qkv(const float (&d)[96], uint32_t base, uint32_t sw, uint32_t scol) {
#pragma unroll
  for (int jj = 0; jj < NJ; jj++) {
    const float f = jj < NQ ? kQScale : 1.f;
    stsm4(base + (jj >> 1) * 8192 + ((((jj & 1) * 2 + scol) ^ sw) << 4), pack_bf16(d[8 * jj] * f, d[8 * jj + 1] * f),
          pack_bf16(d[8 * jj + 2] * f, d[8 * jj + 3] * f), pack_bf16(d[8 * jj + 4] * f, d[8 * jj + 5] * f),
          pack_bf16(d[8 * jj + 6] * f, d[8 * jj + 7] * f));
  }
}
__device__ __forceinline__ void epi_qkv_ln(const float (&d)[96], uint32_t cs_addr, float2 s0, float2 s1, uint32_t base,
                                           uint32_t sw, uint32_t scol) {
#pragma unroll
  for (int jj = 0; jj < 6; jj++) {
    const float f0 = jj < 2 ? kQScale * s0.y : s0.y, f1 = jj < 2 ? kQScale * s1.y : s1.y;
    float c[4];
    float e[4];
    asm volatile("ld.shared.v2.f32 {%0, %1}, [%2];\n" : "=f"(c[0]), "=f"(c[1]) : "r"(cs_addr + jj * 64));
    asm volatile("ld.shared.v2.f32 {%0, %1}, [%2];\n" : "=f"(c[2]), "=f"(c[3]) : "r"(cs_addr + jj * 64 + 32));
    asm volatile("ld.shared.v2.f32 {%0, %1}, [%2];\n" : "=f"(e[0]), "=f"(e[1]) : "r"(cs_addr + jj * 64 + 384));
    asm volatile("ld.shared.v2.f32 {%0, %1}, [%2];\n" : "=f"(e[2]), "=f"(e[3]) : "r"(cs_addr + jj * 64 + 416));
#pragma unroll
    for (int i = 0; i < 4; i++) c[i] += e[i];
    float v[8];
#pragma unroll
    for (int i = 0; i < 8; i++) {
      const float ci = c[(i >> 2) * 2 + (i & 1)];
      v[i] = (i & 2) ? fmaf(-s1.x, ci, d[8 * jj + i]) * f1 : fmaf(-s0.x, ci, d[8 * jj + i]) * f0;
    }
    stsm4(base + (jj >> 1) * 8192 + ((((jj & 1) * 2 + scol) ^ sw) << 4), pack_bf16(v[0], v[1]), pack_bf16(v[2], v[3]),
          pack_bf16(v[4], v[5]), pack_bf16(v[6], v[7]));
  }
}
template <int J0, int J1>
__device__ __forceinline__ void epi_relu(const float (&d)[96], uint32_t base, uint32_t sw, uint32_t scol) {
#pragma unroll
  for (int jj = J0; jj < J1; jj++)
    stsm4(base + ((jj - J0) >> 2) * 16384 + (((((jj - J0) & 3) * 2 + scol) ^ sw) << 4), pack_bf16_relu(d[8 * jj], d[8 * jj + 1]),
          pack_bf16_relu(d[8 * jj + 2], d[8 * jj + 3]), pack_bf16_relu(d[8 * jj + 4], d[8 * jj + 5]),
          pack_bf16_relu(d[8 * jj + 6], d[8 * jj + 7]));
}
__device__ __forceinline__ void epi_out(const float (&d)[96], uint32_t base, uint32_t sw, uint32_t scol) {
#pragma unroll
  for (int jj = 0; jj < 8; jj++) {
    const uint32_t a = base + (jj >> 2) * 16384 + ((((jj & 3) * 2 + scol) ^ sw) << 4);
    uint32_t x0, x1, x2, x3;
    ldsm4(a, x0, x1, x2, x3);
    stsm4(a, pack_bf16(d[8 * jj] + bf_lo(x0), d[8 * jj + 1] + bf_hi(x0)), pack_bf16(d[8 * jj + 2] + bf_lo(x1), d[8 * jj + 3] + bf_hi(x1)),
          pack_bf16(d[8 * jj + 4] + bf_lo(x2), d[8 * jj + 5] + bf_hi(x2)), pack_bf16(d[8 * jj + 6] + bf_lo(x3), d[8 * jj + 7] + bf_hi(x3)));
  }
}

__device__ __noinline__ void attn_exact(float* o_out, uint32_t q_smem_row_addr, const uint8_t* kv_head) {
  const int lane = threadIdx.x & 31, g = lane >> 2, t = lane & 3;
  uint32_t qa[2][4];
  {
    const int r = (lane & 7) + ((lane >> 3) & 1) * 8;
#pragma unroll
    for (int k = 0; k < 2; k++) {
      const int c16 = 2 * k + (lane >> 4);
      ldsm4(q_smem_row_addr + r * 64 + ((c16 ^ ((r >> 1) & 3)) << 4), qa[k][0], qa[k][1], qa[k][2], qa[k][3]);
    }
  }
  float o[16];
#pragma unroll
  for (int i = 0; i < 16; i++) o[i] = 0.f;
  float m0 = -INFINITY, m1 = -INFINITY, l0 = 0.f, l1 = 0.f;
#pragma unroll 1
  for (int kc = 0; kc < kS / 16; kc++) {
    const uint8_t* kt = kv_head + (kc >> 2) * 8192;
    const int k0 = (kc & 3) * 16;
    float s[2][4];
#pragma unroll
    for (int nb = 0; nb < 2; nb++) {
      s[nb][0] = s[nb][1] = s[nb][2] = s[nb][3] = 0.f;
      const int key = k0 + nb * 8 + g;
#pragma unroll
      for (int k = 0; k < 2; k++) {
        const uint32_t b0 = __ldcg((const uint32_t*)(kt + key * 64 + (((2 * k) ^ ((key >> 1) & 3)) << 4) + t * 4));
        const uint32_t b1 = __ldcg((const uint32_t*)(kt + key * 64 + (((2 * k + 1) ^ ((key >> 1) & 3)) << 4) + t * 4));
        asm volatile(
            "mma.sync.aligned.m16n8k16.row.col.f32.bf16.bf16.f32 {%0,%1,%2,%3}, {%4,%5,%6,%7}, {%8,%9}, {%0,%1,%2,%3};\n"
            : "+f"(s[nb][0]), "+f"(s[nb][1]), "+f"(s[nb][2]), "+f"(s[nb][3])
            : "r"(qa[k][0]), "r"(qa[k][1]), "r"(qa[k][2]), "r"(qa[k][3]), "r"(b0), "r"(b1));
      }
    }
    float x0 = fmaxf(fmaxf(s[0][0], s[0][1]), fmaxf(s[1][0], s[1][1]));
    float x1 = fmaxf(fmaxf(s[0][2], s[0][3]), fmaxf(s[1][2], s[1][3]));
    x0 = fmaxf(x0, __shfl_xor_sync(~0u, x0, 1)); x1 = fmaxf(x1, __shfl_xor_sync(~0u, x1, 1));
    x0 = fmaxf(x0, __shfl_xor_sync(~0u, x0, 2)); x1 = fmaxf(x1, __shfl_xor_sync(~0u, x1, 2));
    x0 = fmaxf(x0, m0); x1 = fmaxf(x1, m1);
    const float c0 = ex2(m0 - x0), c1 = ex2(m1 - x1);
    m0 = x0; m1 = x1;
    uint32_t p[4];
    {
      const float e00 = ex2(s[0][0] - m0), e01 = ex2(s[0][1] - m0), e02 = ex2(s[0][2] - m1), e03 = ex2(s[0][3] - m1);
      const float e10 = ex2(s[1][0] - m0), e11 = ex2(s[1][1] - m0), e12 = ex2(s[1][2] - m1), e13 = ex2(s[1][3] - m1);
      l0 = l0 * c0 + (e00 + e01 + e10 + e11);
      l1 = l1 * c1 + (e02 + e03 + e12 + e13);
      p[0] = pack_bf16(e00, e01); p[1] = pack_bf16(e02, e03); p[2] = pack_bf16(e10, e11); p[3] = pack_bf16(e12, e13);
    }
    const uint8_t* vt = kt + 4096;
#pragma unroll
    for (int nb = 0; nb < 4; nb++) {
      uint32_t hv[4];
#pragma unroll
      for (int i = 0; i < 4; i++) {
        const int key = k0 + 2 * t + (i & 1) + (i >> 1) * 8;
        hv[i] = __ldcg((const unsigned short*)(vt + key * 64 + ((nb ^ ((key >> 1) & 3)) << 4) + g * 2));
      }
      const uint32_t b0 = hv[0] | (hv[1] << 16), b1 = hv[2] | (hv[3] << 16);
      o[4 * nb] *= c0; o[4 * nb + 1] *= c0; o[4 * nb + 2] *= c1; o[4 * nb + 3] *= c1;
      asm volatile(
          "mma.sync.aligned.m16n8k16.row.col.f32.bf16.bf16.f32 {%0,%1,%2,%3}, {%4,%5,%6,%7}, {%8,%9}, {%0,%1,%2,%3};\n"
          : "+f"(o[4 * nb]), "+f"(o[4 * nb + 1]), "+f"(o[4 * nb + 2]), "+f"(o[4 * nb + 3])
          : "r"(p[0]), "r"(p[1]), "r"(p[2]), "r"(p[3]), "r"(b0), "r"(b1));
    }
  }
  l0 += __shfl_xor_sync(~0u, l0, 1); l1 += __shfl_xor_sync(~0u, l1, 1);
  l0 += __shfl_xor_sync(~0u, l0, 2); l1 += __shfl_xor_sync(~0u, l1, 2);
  const float i0 = 1.f / l0, i1 = 1.f / l1;
#pragma unroll
  for (int nb = 0; nb < 4; nb++) {
    o_out[4 * nb] = o[4 * nb] * i0; o_out[4 * nb + 1] = o[4 * nb + 1] * i0;
    o_out[4 * nb + 2] = o[4 * nb + 2] * i1; o_out[4 * nb + 3] = o[4 * nb + 3] * i1;
  }
}

struct Params {
  CUtensorMap wqkv1, wqkv2, w1a, w1c, w2, wo, x, out;
  const __nv_bfloat16* xptr;
  const uint8_t *wqkv_p, *w1_p, *w2_p, *wo_p;
};

__global__ void __cluster_dims__(2, 1, 1) __launch_bounds__(kThreads, 1) fused_block_kernel(const __grid_constant__ Params P) {
  extern __shared__ __align__(1024) uint8_t smem_raw[];
  const uint32_t sb = (smem_u32(smem_raw) + 1023) & ~1023u;
  const uint32_t bars = sb + kBarOff;
  const int warp = __shfl_sync(~0u, threadIdx.x >> 5, 0);
  const int lane = threadIdx.x & 31;
  const uint32_t rank = blockIdx.x & 1;
  const int cl = blockIdx.x >> 1;
  const int c = ((cl & 1) << 2) | ((cl >> 3) & 3);
  const int m = (((cl & 6) | (cl >> 5)) << 1) + rank;
  TM(threadIdx.x == 0, 0);

  if (threadIdx.x == 0) {
    for (int i = 0; i < 4; i++) { mbar_init(bars + (B_GFULL + i) * 8, 1); mbar_init(bars + (B_GEMPTY + i) * 8, 8); }
    for (int i = 0; i < (int)kNKv; i++) { mbar_init(bars + (B_KVFULL + i) * 8, 1); mbar_init(bars + (B_KVEMPTY + i) * 8, 16); }
    for (int i = 0; i < 2; i++) { mbar_init(bars + (B_QFULL + i) * 8, 1); mbar_init(bars + (B_QEMPTY + i) * 8, 1); mbar_init(bars + (B_GST + i) * 8, 4); }
    for (int i = 0; i < 4; i++) mbar_init(bars + (B_AST + i) * 8, 4);
    mbar_init(bars + B_STAT * 8, 1);
    asm volatile("fence.mbarrier_init.release.cluster;\n" ::: "memory");
  }
  if (ONES && threadIdx.x >= 256) {
    asm volatile("st.shared.b32 [%0], %1;\n" ::"r"(sb + kOnesOff + (threadIdx.x - 256) * 4), "r"(0x3f803f80u) : "memory");
    fence_async_smem();
  }
  __syncthreads();
  cluster_arrive();

  if (warp < 4) {
    asm volatile("setmaxnreg.dec.sync.aligned.u32 40;\n");
    if (warp == 1 && lane == 0) { prefetch_map(&P.wqkv1); prefetch_map(&P.wqkv2); prefetch_map(&P.w1c); prefetch_map(&P.w1a); prefetch_map(&P.w2); prefetch_map(&P.wo); }
    if (warp == 0 && lane == 0) {
      for (int s = 0; s < 4; s++) {
        mbar_expect_tx(bars + (B_GFULL + s) * 8, 16384 + 12288);
        tma_2d(sb + s * kSlot, &P.x, s * 64, 128 * m, bars + (B_GFULL + s) * 8);
      }
    }
    if (warp == 2 && lane == 0) prefetch_map(&P.out);
    __syncwarp();
    cluster_wait();
    const bool lead = elect_one();
    {
      if (warp == 0) {
        uint32_t ph = 0xf, r3 = 0;
        const uint64_t pol = policy_evict_first();
        uint32_t full, dst;
        auto acquire = [&](int pos, bool first, uint32_t bytes) {
          const uint32_t s = next_slot(pos, first, r3);
          full = bars + s * 8;
          dst = sb + s * kSlot;
          const uint32_t par = (ph >> s) & 1;
          ph ^= 1u << s;
          mbar_wait_sleepy(full + B_GEMPTY * 8, par);
          if (bytes) if (lead) mbar_expect_tx(full, bytes);
        };
        const int kr = rank * 32;
#pragma unroll 1
        for (int kb = 0; kb < 16; kb++) {
          acquire(kb, true, kb >= 4 ? 16384 + 12288 : 0);
          if (lead) tma_4d_mc(dst + 16384 + rank * 6144, &P.wqkv1, 32 * c, kb * 64 + kr, 0, 0, full, pol);
          if (kb >= 4) if (lead) tma_2d(dst, &P.x, kb * 64, 128 * m, full);
          if (PFD && kb == 3) {
            if (lead) tma_pf_4d(&P.wqkv1, 32 * c, (4 + (m >> 1)) * 64 + kr, 0, 0);
            if (m < 8) if (lead) tma_pf_4d(&P.wqkv1, 32 * c, (12 + (m >> 1)) * 64 + kr, 0, 0);
          }
        }
        const uint8_t* xn = g_xn + (size_t)m * 16 * 16384;
#pragma unroll 1
        for (int kb = 0; kb < 16; kb++) {
          acquire(kb, false, 16384 + 24576);
          if (lead) tma_4d_mc(dst + 16384 + rank * 12288, &P.wqkv2, 32 * c, kb * 64 + kr, 1, 0, full, pol);
          if (kb == 0) { flag_wait(&g_flags[(F_XN + m) * 32], 64); TM(lead, 1); }
          if (lead) bulk_g2s(dst, xn + kb * 16384, 16384, full);
        }
#pragma unroll 1
        for (int kb = 0; kb < 16; kb++) {
          acquire(kb, false, 16384 + 20480);
          if (lead) bulk_g2s(dst, xn + kb * 16384, 16384, full);
          if (lead) tma_4d_mc(dst + 16384 + rank * 10240, &P.wqkv1, 32 * c, kb * 64 + kr, 3, 0, full, pol);
          if (lead) tma_3d_mc(dst + 16384 + rank * 10240 + 6144, &P.w1c, 0, kb * 64 + kr, 14 * c, full, pol);
        }
#pragma unroll 1
        for (int i = 0; i < 32; i++) {
          const int kb = i & 15;
          acquire(kb, false, 16384 + 24576);
          if (lead) bulk_g2s(dst, xn + kb * 16384, 16384, full);
          if (lead) tma_3d_mc(dst + 16384 + rank * 12288, &P.w1a, 0, kb * 64 + kr, 7 * c + 1 + (i >> 4) * 3, full, pol);
        }
        const uint8_t* hb = g_h + (size_t)m * 56 * 16384;
        const uint8_t* ob = g_o + (size_t)m * 32 * 8192;
        int pos = 0;
        auto out_h = [&](int n, int hk, int run, int skip, const unsigned* flag) {
          int cnt = 0;
#pragma unroll 1
          for (int i = 0; i < n; i++, pos++) {
            acquire(pos, false, 32768);
            if (lead) tma_3d_mc(dst + 16384 + rank * 8192, &P.w2, 0, hk * 64 + kr, 2 * c, full, pol);
            if (i == 0) flag_wait(flag, 16);
            if (lead) bulk_g2s(dst, hb + hk * 16384, 16384, full);
            hk++;
            if (++cnt == run) { cnt = 0; hk += skip; }
          }
        };
        auto out_o = [&](int j0, int j1) {
#pragma unroll 1
          for (int j = j0; j < j1; j++, pos++) {
            acquire(pos, false, 32768);
            if (lead) tma_3d_mc(dst + 16384 + rank * 8192, &P.wo, 0, j * 64 + kr, 2 * c, full, pol);
            if ((j & 3) == 0) flag_wait(&g_flags[(F_O + m * 4 + (j >> 2)) * 32], 16);
            if (lead) bulk_g2s(dst, ob + j * 16384, 16384, full);
          }
        };
        out_h(8, 0, 1, 6, &g_flags[(F_H + m * 3 + 0) * 32]);
        out_h(24, 1, 3, 4, &g_flags[(F_H + m * 3 + 1) * 32]);
        out_o(0, 8);
        out_h(24, 4, 3, 4, &g_flags[(F_H + m * 3 + 2) * 32]);
        out_o(8, 16);
        acquire(72, false, 32768);
        if (lead) tma_2d(dst, &P.x, 128 * c, 128 * m, full);
        if (lead) tma_2d(dst + 16384, &P.x, 128 * c + 64, 128 * m, full);
      } else if (warp == 1) {
        flag_wait(&g_flags[(F_XN + m) * 32], 64);
        if (lead) mbar_expect_tx(bars + B_STAT * 8, 1024 + 768);
        if (lead) bulk_g2s(sb + kQOff + 8192, g_stat + m * 128, 1024, bars + B_STAT * 8);
        uint32_t ph = 1, full = bars + B_KVFULL * 8, dst = sb + kKvOff + rank * 4096;
        const uint8_t* src = g_kv + (size_t)c * 32 * 8192 + rank * 4096;
#pragma unroll 1
        for (int g = 0; g <= 128; g++) {
          if ((g & 31) == 0 && g < 128) {
            const int u = g >> 5, head = 8 * u + c;
            flag_wait(&g_flags[(F_KV + head) * 32], 32);
            TM(lead, 2 + u);
            if (u >= 2) mbar_wait_sleepy(bars + (B_QEMPTY + (u & 1)) * 8, 0);
            if (lead) mbar_expect_tx(bars + (B_QFULL + (u & 1)) * 8, 8192);
            if (lead) bulk_g2s(sb + kQOff + (u & 1) * 8192, g_q + ((size_t)head * kS + m * 128) * 64, 8192, bars + (B_QFULL + (u & 1)) * 8);
          }
          mbar_wait_sleepy(full + (B_KVEMPTY - B_KVFULL) * 8, ph);
          if (lead) mbar_expect_tx(full, 8192);
          if (lead) bulk_g2s_mc(dst, src, 4096, full);
          const int t = g + 1 - (int)rank;
          if (t > 0 && t < 128) src += (t & 31) ? 8192 : 8192 + 7 * 32 * 8192;
          full += 8;
          dst += 8192;
          if (full == bars + (B_KVFULL + kNKv) * 8) { full -= kNKv * 8; dst -= kNKv * 8192; ph ^= 1; }
        }
      } else if (lane != 0) {
      } else if (warp == 2) {
        const uint32_t st = sb + kStageOff;
#pragma unroll 1
        for (int t = 0; t < 5; t++) {
#pragma unroll 1
          for (int h = 0; h < 2; h++) {
            mbar_wait_sleepy(bars + (B_GST + h) * 8, t & 1);
            if (t < 3) {
              const int nr = t == 1 ? 2 : 1;
              for (int r = 0; r < nr; r++) {
                const int head = 8 * (t == 2 ? 3 : t + r) + c;
                bulk_s2g(g_q + ((size_t)head * kS + m * 128 + h * 64) * 64, st + r * 8192 + h * 4096, 4096);
                uint8_t* kv = g_kv + ((size_t)head * 32 + 2 * m + h) * 8192;
                bulk_s2g(kv, st + (nr + r) * 8192 + h * 4096, 4096);
                bulk_s2g(kv + 4096, st + (2 * nr + r) * 8192 + h * 4096, 4096);
              }
              if (t == 2) bulk_s2g(g_h + ((size_t)m * 56 + 7 * c) * 16384 + h * 8192, st + 24576 + h * 8192, 8192);
            } else {
              for (int a = 0; a < 3; a++)
                bulk_s2g(g_h + ((size_t)m * 56 + 7 * c + 3 * t - 8 + a) * 16384 + h * 8192, st + a * 16384 + h * 8192, 8192);
            }
            bulk_commit();
          }
          bulk_wait_read();
          TM(t < 2, 52 + 2 * t);
          mbar_arrive_cta(bars + (B_GEMPTY + 3) * 8, 0, 4);
          mbar_arrive_cta(bars + (B_GEMPTY + 3) * 8, 1, 4);
          bulk_wait_all();
          TM(t < 2, 53 + 2 * t);
          if (t < 3) flag_add(&g_flags[(F_KV + 8 * (t == 2 ? 3 : t) + c) * 32], 2);
          if (t == 1) flag_add(&g_flags[(F_KV + 16 + c) * 32], 2);
          if (t >= 2) flag_add(&g_flags[(F_H + m * 3 + t - 2) * 32], 2);
          TM(true, 8 + t);
        }
#pragma unroll 1
        for (int h = 0; h < 2; h++) {
          mbar_wait_sleepy(bars + (B_GST + h) * 8, 1);
          tma_store_2d(&P.out, sb + kOutSlot * kSlot + h * 8192, 128 * c, 128 * m + 64 * h);
          tma_store_2d(&P.out, sb + kOutSlot * kSlot + 16384 + h * 8192, 128 * c + 64, 128 * m + 64 * h);
          bulk_commit();
        }
        bulk_wait_all();
        TM(true, 13);
      } else {
        if (PREF & 1) {
          for (int i = 0; i < 6; i++) l2_prefetch(P.wqkv_p + (size_t)blockIdx.x * 49152 + i * 8192, 8192);
          for (int i = 0; i < 7; i++) l2_prefetch(P.w1_p + (size_t)blockIdx.x * 57344 + i * 8192, 8192);
        }
#pragma unroll 1
        for (int u = 0; u < 4; u++) {
          for (int w = 0; w < 2; w++) {
            mbar_wait_sleepy(bars + (B_AST + w * 2 + (u & 1)) * 8, u >> 1);
            bulk_s2g(g_o + ((size_t)m * 32 + 8 * u + c) * 8192 + w * 4096, sb + kQOff + (u & 1) * 8192 + w * 4096, 4096);
            bulk_commit();
          }
          bulk_wait_read();
          mbar_arrive(bars + (B_QEMPTY + (u & 1)) * 8);
          bulk_wait_all();
          flag_add(&g_flags[(F_O + m * 4 + u) * 32], 2);
          TM(true, 14 + u);
          if ((PREF & 2) && u == 0) {
            for (int i = 0; i < 7; i++) l2_prefetch(P.w2_p + (size_t)blockIdx.x * 57344 + i * 8192, 8192);
            for (int i = 0; i < 2; i++) l2_prefetch(P.wo_p + (size_t)blockIdx.x * 16384 + i * 8192, 8192);
          }
        }
      }
    }
    __syncwarp();
  } else if (warp < 8) {
    asm volatile("setmaxnreg.inc.sync.aligned.u32 240;\n");
    cluster_wait();
    const int w = warp & 3;
    const bool rel_lane = lane < 2;
    const uint32_t rel_addr = mapa(bars + B_GEMPTY * 8, lane & 1);
    uint32_t phases = 0, r3 = 0, twait = 0;
    uint32_t lo0 = (sb & 0x3FFFF) >> 4;
    asm volatile("" : "+r"(lo0));
    lo0 = __shfl_sync(~0u, lo0, 0);
    const uint32_t srow = w * 16 + (lane & 7) + ((lane >> 3) & 1) * 8, scol = lane >> 4;
    const uint32_t st = sb + kStageOff;
    const uint32_t gst0 = bars + B_GST * 8, gst1 = gst0 + 8;
    const uint32_t b64 = st + srow * 64, sw64 = (srow >> 1) & 3, b128 = srow * 128, sw128 = srow & 7;
    float d0[96], d1[96], cs[3] = {0.f, 0.f, 0.f};
#pragma unroll
    for (int i = 0; i < 96; i++) { d0[i] = 0.f; d1[i] = 0.f; }
    gemm_first(d0, d1, cs, sb, bars, rank, rel_addr, rel_lane, twait);
    TM(threadIdx.x == 128, 20);
    const uint32_t csb = sb + kQOff + 8192 + 1024;
#pragma unroll
    for (int i = 0; i < 3; i++) {
      cs[i] += __shfl_xor_sync(~0u, cs[i], 1);
      cs[i] += __shfl_xor_sync(~0u, cs[i], 2);
      if ((lane & 3) < 2)
        asm volatile("st.async.weak.shared::cluster.mbarrier::complete_tx::bytes.b32 [%0], %1, [%2];\n" ::"r"(
                         mapa(csb + rank * 384 + ((3 * w + i) * 8 + (lane >> 2)) * 4, lane & 1)),
                     "r"(__float_as_uint(cs[i])), "r"(mapa(bars + B_STAT * 8, lane & 1))
                     : "memory");
    }
    named_sync(1);
    mbar_wait(bars + B_STAT * 8, 0);
    {
      float2 sv[4];
#pragma unroll
      for (int i = 0; i < 4; i++)
        asm volatile("ld.shared.v2.f32 {%0, %1}, [%2];\n" : "=f"(sv[i].x), "=f"(sv[i].y)
                     : "r"(sb + kQOff + 8192 + ((i >> 1) * 64 + w * 16 + (lane >> 2) + (i & 1) * 8) * 8));
      epi_qkv_ln(d0, csb + (lane & 3) * 8, sv[0], sv[1], b64, sw64, scol);
      epi_publish(gst0, lane);
      epi_qkv_ln(d1, csb + (lane & 3) * 8, sv[2], sv[3], b64 + 4096, sw64, scol);
      epi_publish(gst1, lane);
    }
    TM(threadIdx.x == 128, 26);
    gemm_mainloop<192, 16, GD192, false>(d0, d1, lo0, bars, phases, r3, 2048, desc_hi(512, 2), 1024 >> 4, 12288 >> 4, rel_addr, rel_lane, twait);
    TM(threadIdx.x == 128, 21);
    named_sync(1);
    epi_qkv<12, 4>(d0, b64, sw64, scol);
    epi_publish(gst0, lane);
    epi_qkv<12, 4>(d1, b64 + 4096, sw64, scol);
    epi_publish(gst1, lane);
    TM(threadIdx.x == 128, 27);
    gemm_mainloop<160, 16, GD192, false>(d0, d1, lo0, bars, phases, r3, 2048, desc_hi(512, 2), 1024 >> 4, 10240 >> 4, rel_addr, rel_lane, twait);
    TM(threadIdx.x == 128, 22);
    named_sync(1);
    epi_qkv<6, 2>(d0, b64, sw64, scol);
    epi_relu<6, 10>(d0, st + 24576 + b128, sw128, scol);
    epi_publish(gst0, lane);
    epi_qkv<6, 2>(d1, b64 + 4096, sw64, scol);
    epi_relu<6, 10>(d1, st + 24576 + 8192 + b128, sw128, scol);
    epi_publish(gst1, lane);
#pragma unroll 1
    for (int t = 3; t < 5; t++) {
      gemm_mainloop<192, 16, GD192, false>(d0, d1, lo0, bars, phases, r3, 4096, desc_hi(1024, 1), 2048 >> 4, 12288 >> 4, rel_addr, rel_lane, twait);
      TM(threadIdx.x == 128, 20 + t);
      named_sync(1);
      epi_relu<0, 12>(d0, st + b128, sw128, scol);
      epi_publish(gst0, lane);
      epi_relu<0, 12>(d1, st + 8192 + b128, sw128, scol);
      epi_publish(gst1, lane);
    }
    gemm_mainloop<128, 72, GDOUT, true>(d0, d1, lo0, bars, phases, r3, 4096, desc_hi(1024, 1), 2048 >> 4, 8192 >> 4, rel_addr, rel_lane, twait);
    TM(threadIdx.x == 128, 25);
    mbar_wait(bars + (B_GFULL + kOutSlot) * 8, (phases >> kOutSlot) & 1);
    epi_out(d0, sb + kOutSlot * kSlot + b128, sw128, scol);
    epi_publish(gst0, lane);
    epi_out(d1, sb + kOutSlot * kSlot + 8192 + b128, sw128, scol);
    epi_publish(gst1, lane);
  } else {
    asm volatile("setmaxnreg.dec.sync.aligned.u32 112;\n");
    {
      const int r0 = c * 16 + (warp - 8) * 2;
      const uint32_t lnbuf = sb + kKvOff + (warp - 8) * 4096;
      const uint32_t statbuf = sb + kKvOff + 32768 + (warp - 8) * 16;
      uint4 v[2][4];
#pragma unroll
      for (int i = 0; i < 2; i++)
#pragma unroll
        for (int j = 0; j < 4; j++)
          v[i][j] = __ldg(reinterpret_cast<const uint4*>(P.xptr + (size_t)(m * 128 + r0 + i) * kD) + lane + 32 * j);
      TM(threadIdx.x == 256, 56);
#pragma unroll
      for (int i = 0; i < 2; i++) {
        float f[32];
#pragma unroll
        for (int j = 0; j < 4; j++) {
          f[8 * j] = bf_lo(v[i][j].x); f[8 * j + 1] = bf_hi(v[i][j].x); f[8 * j + 2] = bf_lo(v[i][j].y); f[8 * j + 3] = bf_hi(v[i][j].y);
          f[8 * j + 4] = bf_lo(v[i][j].z); f[8 * j + 5] = bf_hi(v[i][j].z); f[8 * j + 6] = bf_lo(v[i][j].w); f[8 * j + 7] = bf_hi(v[i][j].w);
        }
        float sum = 0.f;
#pragma unroll
        for (int j = 0; j < 32; j++) sum += f[j];
#pragma unroll
        for (int o = 16; o; o >>= 1) sum += __shfl_xor_sync(~0u, sum, o);
        const float mean = sum * (1.f / kD);
        TM(threadIdx.x == 256 && i == 0 && mean != 123.f, 57);
        float sq = 0.f;
#pragma unroll
        for (int j = 0; j < 32; j++) { const float dlt = f[j] - mean; sq = fmaf(dlt, dlt, sq); }
#pragma unroll
        for (int o = 16; o; o >>= 1) sq += __shfl_xor_sync(~0u, sq, o);
        const float mb = bf_round(mean);
        const float den = bf_round(sqrtf(bf_round(bf_round(sq * (1.f / kD)) + 1e-5f)));
        const float inv = 1.f / den;
        const int r = r0 + i;
        if (lane == 0) asm volatile("st.shared.v2.f32 [%0], {%1, %2};\n" ::"r"(statbuf + i * 8), "f"(mb), "f"(inv) : "memory");
#pragma unroll
        for (int j = 0; j < 4; j++) {
          uint4 o;
          uint32_t dd[4];
#pragma unroll
          for (int e = 0; e < 4; e++) {
            const uint32_t t = pack_bf16(f[8 * j + 2 * e] - mb, f[8 * j + 2 * e + 1] - mb);
            dd[e] = pack_bf16(bf_lo(t) * inv, bf_hi(t) * inv);
          }
          o.x = dd[0]; o.y = dd[1]; o.z = dd[2]; o.w = dd[3];
          const int ch = lane + 32 * j;
          asm volatile("st.shared.v4.b32 [%0], {%1, %2, %3, %4};\n" ::"r"(lnbuf + (ch >> 3) * 256 + i * 128 + (((ch & 7) ^ (r & 7)) << 4)),
                       "r"(o.x), "r"(o.y), "r"(o.z), "r"(o.w)
                       : "memory");
        }
      }
      TM(threadIdx.x == 256, 58);
      fence_async_smem();
      __syncwarp();
      if (lane < 17) {
        if (lane < 16) bulk_s2g(g_xn + ((size_t)(m * 16 + lane) * 128 + r0) * 128, lnbuf + lane * 256, 256);
        else bulk_s2g(g_stat + m * 128 + r0, statbuf, 16);
        bulk_commit();
        bulk_wait_all();
      }
      __syncwarp();
      if (lane == 0) flag_add(&g_flags[(F_XN + m) * 32], 1);
      TM(threadIdx.x == 256, 59);
    }
    cluster_wait();
    const int aw = (warp - 8) >> 2, w = warp & 3;
    const bool rel_lane = lane < 2;
    const uint32_t rel_addr = mapa(bars + B_KVEMPTY * 8, lane & 1);
    constexpr int NO = ONES ? 20 : 16;
    float s[32], o[NO];
    uint32_t p[16];
#pragma unroll
    for (int i = 0; i < 16; i++) p[i] = 0u;
#pragma unroll
    for (int i = 0; i < NO; i++) o[i] = 0.f;
#pragma unroll
    for (int i = 0; i < 32; i++) s[i] = 0.f;
    float l0 = 0.f, l1 = 0.f;
    const uint32_t hi64 = desc_hi(512, 2);
    const uint32_t kv_lo0 = desc_lo(sb + kKvOff, 16);
    uint32_t st = 0, ph = 0;
    uint32_t rel_cur = rel_addr;
    const uint32_t v_lo0 = desc_lo(sb + kKvOff + 4096, kOnesOff - kKvOff - 4096);
    auto issue_pv = [&](int acc) {
      const uint32_t v_lo = v_lo0 + st * (512u - (512u << 16));
      wgmma_rs_n40<1>(o, p[0], p[1], p[2], p[3], mk_desc(v_lo, hi64), acc);
      wgmma_rs_n40<1>(o, p[4], p[5], p[6], p[7], mk_desc(v_lo + (64u - (64u << 16)), hi64), 1);
      wgmma_rs_n40<1>(o, p[8], p[9], p[10], p[11], mk_desc(v_lo + (128u - (128u << 16)), hi64), 1);
      wgmma_rs_n40<1>(o, p[12], p[13], p[14], p[15], mk_desc(v_lo + (192u - (192u << 16)), hi64), 1);
    };
    auto issue_qk = [&](uint32_t q_lo) {
      const uint32_t k_lo = kv_lo0 + st * 512;
      wgmma_ss_n64<0>(s, mk_desc(q_lo, hi64), mk_desc(k_lo, hi64), 0);
      wgmma_ss_n64<0>(s, mk_desc(q_lo + 2, hi64), mk_desc(k_lo + 2, hi64), 1);
    };
    auto softmax_tile = [&]() {
#pragma unroll
      for (int i = 0; i < 8; i++) {
        const float e0 = ex2(s[4 * i]), e1 = ex2(s[4 * i + 1]), e2 = ex2(s[4 * i + 2]), e3 = ex2(s[4 * i + 3]);
        if (!ONES) { l0 += e0 + e1; l1 += e2 + e3; }
        p[2 * i] = pack_bf16(e0, e1); p[2 * i + 1] = pack_bf16(e2, e3);
      }
    };
    auto advance = [&]() {
      mbar_arrive_cluster_if(rel_cur, rel_lane);
      rel_cur += 8;
      if (++st == kNKv) { st = 0; ph ^= 1; rel_cur = rel_addr; }
    };
#pragma unroll 1
    for (int u = 0; u <= 4; u++) {
      const uint32_t q_lo = desc_lo(sb + kQOff + (u & 1) * 8192 + aw * 4096, 16);
      if (u < 4) mbar_wait(bars + (B_QFULL + (u & 1)) * 8, u >> 1);
      mbar_wait(bars + (B_KVFULL + st) * 8, ph);
      fence_regs(s); fence_regs(o); fence_regs(p);
      wgmma_fence();
      issue_pv(1);
      issue_qk(q_lo);
      wgmma_commit();
      wgmma_wait<0>();
      fence_regs(s); fence_regs(o); fence_regs(p);
      advance();
      if (u > 0) {
        const uint32_t ob = sb + kQOff + ((u - 1) & 1) * 8192 + aw * 4096;
        l0 = o[16]; l1 = o[18];
        bool ok = l0 >= 8.271806e-25f && l0 <= 1.2676506e30f && l1 >= 8.271806e-25f && l1 <= 1.2676506e30f;
#pragma unroll
        for (int i = 0; i < 16; i++) ok = ok && (fabsf(o[i]) <= 3.0e38f);
        const float i0 = 1.f / l0, i1 = 1.f / l1;
        uint32_t r[8];
#pragma unroll
        for (int i = 0; i < 4; i++) {
          r[2 * i] = pack_bf16(o[4 * i] * i0, o[4 * i + 1] * i0);
          r[2 * i + 1] = pack_bf16(o[4 * i + 2] * i1, o[4 * i + 3] * i1);
        }
        if (__any_sync(~0u, !ok)) {
          float e[16];
          attn_exact(e, ob + w * 1024, g_kv + (size_t)(8 * (u - 1) + c) * 32 * 8192);
#pragma unroll
          for (int i = 0; i < 8; i++) r[i] = pack_bf16(e[2 * i], e[2 * i + 1]);
        }
        __syncwarp();
        const uint32_t srow = w * 16 + (lane & 7) + ((lane >> 3) & 1) * 8, scol = lane >> 4;
        const uint32_t base = ob + srow * 64, sw = (srow >> 1) & 3;
        stsm4(base + ((scol ^ sw) << 4), r[0], r[1], r[2], r[3]);
        stsm4(base + (((2 + scol) ^ sw) << 4), r[4], r[5], r[6], r[7]);
        epi_publish(bars + (B_AST + aw * 2 + ((u - 1) & 1)) * 8, lane);
        l0 = 0.f; l1 = 0.f;
        TM(threadIdx.x == 256, 30 + u);
        TPUT(threadIdx.x == 256, 46 + u, clk32());
      }
      if (u == 4) break;
      bool ready = false;
      softmax_tile();
#pragma unroll 1
      for (int j = 1; j < 32; j++) {
        if (!EARLYW || !ready) mbar_wait(bars + (B_KVFULL + st) * 8, ph);
          fence_regs(s); fence_regs(o); fence_regs(p);
        wgmma_fence(); issue_pv(j != 1); issue_qk(q_lo); wgmma_commit(); wgmma_wait<0>();
        fence_regs(s); fence_regs(o); fence_regs(p);
        advance();
        if (EARLYW) ready = mbar_test(bars + (B_KVFULL + st) * 8, ph);
        softmax_tile();
      }
    }
  }

  cluster_arrive();
  cluster_wait();
  if (threadIdx.x == 0) {
    TM(true, 40);
    asm volatile("fence.acq_rel.gpu;\n" ::: "memory");
    const unsigned old = atomicAdd(&g_flags[F_DONE * 32], 1u);
    if (old == kCtas - 1) {
      asm volatile("fence.acq_rel.gpu;\n" ::: "memory");
      for (int i = 0; i < F_COUNT; i++) g_flags[i * 32] = 0u;
    }
  }
}

typedef CUresult (*EncodeFn)(CUtensorMap*, CUtensorMapDataType, cuuint32_t, void*, const cuuint64_t*, const cuuint64_t*,
                             const cuuint32_t*, const cuuint32_t*, CUtensorMapInterleave, CUtensorMapSwizzle,
                             CUtensorMapL2promotion, CUtensorMapFloatOOBfill);

void encode(EncodeFn fn, CUtensorMap* map, const void* base, int rank, const cuuint64_t* dims, const cuuint64_t* strides,
            const cuuint32_t* box, CUtensorMapSwizzle sw) {
  const cuuint32_t es[5] = {1, 1, 1, 1, 1};
  fn(map, CU_TENSOR_MAP_DATA_TYPE_BFLOAT16, rank, const_cast<void*>(base), dims, strides, box, es,
     CU_TENSOR_MAP_INTERLEAVE_NONE, sw, CU_TENSOR_MAP_L2_PROMOTION_L2_256B, CU_TENSOR_MAP_FLOAT_OOB_FILL_NONE);
}

}

extern "C" void kernel_launch(void* const* d_in, const int* in_sizes, int n_in, void* d_out, int out_size) {
  (void)in_sizes; (void)n_in; (void)out_size;
  static Params P;
  static const void* key[6] = {nullptr, nullptr, nullptr, nullptr, nullptr, nullptr};
  const void* cur[6] = {d_in[0], d_in[1], d_in[2], d_in[4], d_in[5], d_out};
  bool same = true;
  for (int i = 0; i < 6; i++) same = same && key[i] == cur[i];
  if (!same) {
    void* fn = nullptr;
    cudaDriverEntryPointQueryResult q;
    cudaGetDriverEntryPoint("cuTensorMapEncodeTiled", &fn, cudaEnableDefault, &q);
    EncodeFn enc = (EncodeFn)fn;
    {
      const cuuint64_t d[4] = {256, 1024, 4, 3}, s[3] = {6144, 512, 2048};
      const cuuint32_t b1[4] = {32, 32, 1, 3}, b2[4] = {32, 32, 2, 3};
      encode(enc, &P.wqkv1, d_in[1], 4, d, s, b1, CU_TENSOR_MAP_SWIZZLE_64B);
      encode(enc, &P.wqkv2, d_in[1], 4, d, s, b2, CU_TENSOR_MAP_SWIZZLE_64B);
    }
    {
      const cuuint64_t d[3] = {64, 1024, 56}, s[2] = {kDff * 2, 128};
      const cuuint32_t b3[3] = {64, 32, 3};
      encode(enc, &P.w1a, d_in[4], 3, d, s, b3, CU_TENSOR_MAP_SWIZZLE_128B);
      const cuuint64_t dc[3] = {32, 1024, 112}, sc[2] = {kDff * 2, 64};
      const cuuint32_t bc[3] = {32, 32, 2};
      encode(enc, &P.w1c, d_in[4], 3, dc, sc, bc, CU_TENSOR_MAP_SWIZZLE_64B);
    }
    {
      const cuuint64_t d2[3] = {64, kDff, 16}, d1[3] = {64, kD, 16}, s[2] = {kD * 2, 128};
      const cuuint32_t b[3] = {64, 32, 2};
      encode(enc, &P.w2, d_in[5], 3, d2, s, b, CU_TENSOR_MAP_SWIZZLE_128B);
      encode(enc, &P.wo, d_in[2], 3, d1, s, b, CU_TENSOR_MAP_SWIZZLE_128B);
    }
    {
      const cuuint64_t d[2] = {kD, kS}, s[1] = {kD * 2};
      const cuuint32_t bx[2] = {64, 128}, bo[2] = {64, 64};
      encode(enc, &P.x, d_in[0], 2, d, s, bx, CU_TENSOR_MAP_SWIZZLE_128B);
      encode(enc, &P.out, d_out, 2, d, s, bo, CU_TENSOR_MAP_SWIZZLE_128B);
    }
    P.xptr = (const __nv_bfloat16*)d_in[0];
    P.wqkv_p = (const uint8_t*)d_in[1];
    P.wo_p = (const uint8_t*)d_in[2];
    P.w1_p = (const uint8_t*)d_in[4];
    P.w2_p = (const uint8_t*)d_in[5];
    cudaFuncSetAttribute(fused_block_kernel, cudaFuncAttributeMaxDynamicSharedMemorySize, kSmemBytes);
    for (int i = 0; i < 6; i++) key[i] = cur[i];
  }
  fused_block_kernel<<<kCtas, kThreads, kSmemBytes>>>(P);
}
```

```cpp
#include <cuda_runtime.h>
#include <cuda_bf16.h>
#include <cuda.h>
#include <stdint.h>

#define GD192 1
#define GDOUT GD128
#define EVF 0
#define PFD 0
#define FIRSTW 0
#define MAPV 2
#define PREF 0
#define ONES 1
#define EARLYW 1
#define GD128 1

namespace {

constexpr int kS = 2048, kD = 1024, kDff = 3584;
constexpr int kThreads = 512;
constexpr int kCtas = 128;

constexpr uint32_t kSlot = 40960;
constexpr uint32_t kStageOff = 3 * kSlot;
constexpr uint32_t kKvOff = 4 * kSlot + 8192;
constexpr uint32_t kNKv = 5;
constexpr uint32_t kQOff = kKvOff + kNKv * 8192;
constexpr uint32_t kBarOff = kQOff + 2 * 8192;
constexpr uint32_t kOnesOff = kBarOff + 512;
constexpr uint32_t kSmemBytes = kOnesOff + 1024 + 1024;
constexpr uint32_t B_GFULL = 0, B_GEMPTY = 4, B_KVFULL = 8, B_KVEMPTY = 13, B_QFULL = 18, B_QEMPTY = 20, B_GST = 22,
                   B_AST = 24, B_STAT = 28, B_GST0 = 29, B_OUT = 30;

__device__ __align__(1024) uint8_t g_xn[16 * 16 * 16384];
__device__ __align__(1024) uint8_t g_q[32 * 2048 * 64];
__device__ __align__(1024) uint8_t g_kv[32 * 32 * 8192];
__device__ __align__(1024) uint8_t g_h[16 * 56 * 16384];
__device__ __align__(1024) uint8_t g_o[16 * 32 * 8192];
__device__ __align__(1024) float2 g_stat[2048];
constexpr int F_XN = 0, F_KV = 16, F_H = 48, F_O = 96, F_DONE = 160, F_COUNT = 161;
__device__ unsigned g_flags[F_COUNT * 32];

__device__ __forceinline__ uint32_t smem_u32(const void* p) { return (uint32_t)__cvta_generic_to_shared(p); }
__device__ __forceinline__ void wgmma_fence() { asm volatile("wgmma.fence.sync.aligned;\n" ::: "memory"); }
__device__ __forceinline__ void wgmma_commit() { asm volatile("wgmma.commit_group.sync.aligned;\n" ::: "memory"); }
template <int N>
__device__ __forceinline__ void wgmma_wait() { asm volatile("wgmma.wait_group.sync.aligned %0;\n" ::"n"(N) : "memory"); }
template <int N>
__device__ __forceinline__ void fence_regs(float (&r)[N]) {
#pragma unroll
  for (int i = 0; i < N; i++) asm volatile("" : "+f"(r[i])::"memory");
}
template <int N>
__device__ __forceinline__ void fence_regs(uint32_t (&r)[N]) {
#pragma unroll
  for (int i = 0; i < N; i++) asm volatile("" : "+r"(r[i])::"memory");
}
__device__ __forceinline__ uint64_t mk_desc(uint32_t lo, uint32_t hi) { return ((uint64_t)hi << 32) | lo; }
__host__ __device__ constexpr uint32_t desc_hi(uint32_t sbo, uint32_t swz) { return (sbo >> 4) | (swz << 30); }
__device__ __forceinline__ uint32_t desc_lo(uint32_t addr, uint32_t lbo) { return ((addr & 0x3FFFF) >> 4) | ((lbo >> 4) << 16); }

__device__ __forceinline__ void mbar_init(uint32_t bar, uint32_t cnt) {
  asm volatile("mbarrier.init.shared::cta.b64 [%0], %1;\n" ::"r"(bar), "r"(cnt) : "memory");
}
__device__ __forceinline__ void mbar_expect_tx(uint32_t bar, uint32_t bytes) {
  asm volatile("mbarrier.arrive.expect_tx.shared::cta.b64 _, [%0], %1;\n" ::"r"(bar), "r"(bytes) : "memory");
}
__device__ __forceinline__ void mbar_arrive(uint32_t bar) {
  asm volatile("mbarrier.arrive.shared::cta.b64 _, [%0];\n" ::"r"(bar) : "memory");
}
__device__ __forceinline__ void mbar_arrive_cta(uint32_t bar, uint32_t cta, uint32_t cnt) {
  asm volatile(
      "{\n.reg .b32 ra;\nmapa.shared::cluster.u32 ra, %0, %1;\nmbarrier.arrive.shared::cluster.b64 _, [ra], %2;\n}\n" ::"r"(bar),
      "r"(cta), "r"(cnt)
      : "memory");
}
__device__ __forceinline__ bool mbar_test(uint32_t bar, uint32_t parity) {
  uint32_t ok;
  asm volatile("{\n.reg .pred p;\nmbarrier.test_wait.parity.shared::cta.b64 p, [%1], %2;\nselp.u32 %0, 1, 0, p;\n}\n"
               : "=r"(ok)
               : "r"(bar), "r"(parity)
               : "memory");
  return ok;
}
__device__ __forceinline__ void mbar_wait(uint32_t bar, uint32_t parity) {
  asm volatile(
      "{\n.reg .pred p, q;\n.reg .u32 it;\nmov.u32 it, 0;\n"
      "LW_%=:\n"
      "mbarrier.try_wait.parity.shared::cta.b64 p, [%0], %1;\n"
      "@p bra LD_%=;\n"
      "add.u32 it, it, 1;\n"
      "setp.lt.u32 q, it, 0x400000;\n"
      "@q bra LW_%=;\n"
      "trap;\n"
      "LD_%=:\n}\n" ::"r"(bar), "r"(parity) : "memory");
}
__device__ __forceinline__ void mbar_wait_sleepy(uint32_t bar, uint32_t parity) {
  asm volatile(
      "{\n.reg .pred p, q;\n.reg .u32 it;\nmov.u32 it, 0;\n"
      "LW_%=:\n"
      "mbarrier.try_wait.parity.shared::cta.b64 p, [%0], %1, 20000;\n"
      "@p bra LD_%=;\n"
      "add.u32 it, it, 1;\n"
      "setp.lt.u32 q, it, 0x400000;\n"
      "@q bra LW_%=;\n"
      "trap;\n"
      "LD_%=:\n}\n" ::"r"(bar), "r"(parity) : "memory");
}
__device__ __forceinline__ uint32_t mapa(uint32_t addr, uint32_t cta) {
  uint32_t r;
  asm("mapa.shared::cluster.u32 %0, %1, %2;\n" : "=r"(r) : "r"(addr), "r"(cta));
  return r;
}
__device__ __forceinline__ void mbar_arrive_cluster_if(uint32_t addr, bool pred) {
  asm volatile("{\n.reg .pred p;\nsetp.ne.u32 p, %1, 0;\n@p mbarrier.arrive.shared::cluster.b64 _, [%0];\n}\n" ::"r"(addr),
               "r"((uint32_t)pred)
               : "memory");
}
__device__ __forceinline__ void flag_wait(const unsigned* f, unsigned target) {
  uint32_t it = 0;
#pragma unroll 1
  while (true) {
    unsigned v;
    asm volatile("ld.acquire.gpu.global.u32 %0, [%1];\n" : "=r"(v) : "l"(f) : "memory");
    if (v >= target) break;
    if (++it > (1u << 22)) asm volatile("trap;");
  }
  asm volatile("fence.proxy.async.global;\n" ::: "memory");
}
__device__ __forceinline__ void flag_add(unsigned* f, unsigned v) {
  asm volatile("red.relaxed.gpu.global.add.u32 [%0], %1;\n" ::"l"(f), "r"(v) : "memory");
}
__device__ __forceinline__ bool elect_one() {
  uint32_t p;
  asm volatile("{\n.reg .pred P;\nelect.sync _|P, 0xffffffff;\nselp.u32 %0, 1, 0, P;\n}\n" : "=r"(p));
  return p;
}
__device__ __forceinline__ void bulk_g2s(uint32_t dst, const void* src, uint32_t bytes, uint32_t bar) {
  asm volatile("cp.async.bulk.shared::cluster.global.mbarrier::complete_tx::bytes [%0], [%1], %2, [%3];\n" ::"r"(dst),
               "l"(src), "r"(bytes), "r"(bar)
               : "memory");
}
__device__ __forceinline__ void bulk_g2s_mc(uint32_t dst, const void* src, uint32_t bytes, uint32_t bar) {
  asm volatile(
      "cp.async.bulk.shared::cluster.global.mbarrier::complete_tx::bytes.multicast::cluster [%0], [%1], %2, [%3], %4;\n" ::"r"(dst),
      "l"(src), "r"(bytes), "r"(bar), "h"((uint16_t)3)
      : "memory");
}
__device__ __forceinline__ void bulk_s2g(void* dst, uint32_t src, uint32_t bytes) {
  asm volatile("cp.async.bulk.global.shared::cta.bulk_group [%0], [%1], %2;\n" ::"l"(dst), "r"(src), "r"(bytes) : "memory");
}
__device__ __forceinline__ void l2_prefetch(const void* src, uint32_t bytes) {
  asm volatile("cp.async.bulk.prefetch.L2.global [%0], %1;\n" ::"l"(src), "r"(bytes) : "memory");
}
__device__ __forceinline__ void bulk_commit() { asm volatile("cp.async.bulk.commit_group;\n" ::: "memory"); }
__device__ __forceinline__ void bulk_wait_read() { asm volatile("cp.async.bulk.wait_group.read 0;\n" ::: "memory"); }
__device__ __forceinline__ void bulk_wait_all() { asm volatile("cp.async.bulk.wait_group 0;\n" ::: "memory"); }
__device__ __forceinline__ void tma_2d(uint32_t dst, const CUtensorMap* m, int c0, int c1, uint32_t bar) {
  asm volatile(
      "cp.async.bulk.tensor.2d.shared::cluster.global.mbarrier::complete_tx::bytes [%0], [%1, {%3, %4}], [%2];\n" ::"r"(dst),
      "l"((uint64_t)m), "r"(bar), "r"(c0), "r"(c1)
      : "memory");
}
__device__ __forceinline__ uint64_t policy_evict_first() {
  uint64_t p;
  asm volatile("createpolicy.fractional.L2::evict_first.b64 %0, 1.0;\n" : "=l"(p));
  return p;
}
__device__ __forceinline__ void tma_3d_mc(uint32_t dst, const CUtensorMap* m, int c0, int c1, int c2, uint32_t bar, uint64_t pol) {
  asm volatile(
      "cp.async.bulk.tensor.3d.shared::cluster.global.mbarrier::complete_tx::bytes.multicast::cluster [%0], [%1, {%3, %4, %5}], "
      "[%2], %6;\n" ::"r"(dst),
      "l"((uint64_t)m), "r"(bar), "r"(c0), "r"(c1), "r"(c2), "h"((uint16_t)3)
      : "memory");
}
__device__ __forceinline__ void tma_4d_mc(uint32_t dst, const CUtensorMap* m, int c0, int c1, int c2, int c3, uint32_t bar, uint64_t pol) {
  asm volatile(
      "cp.async.bulk.tensor.4d.shared::cluster.global.mbarrier::complete_tx::bytes.multicast::cluster [%0], [%1, {%3, %4, %5, "
      "%6}], [%2], %7;\n" ::"r"(dst),
      "l"((uint64_t)m), "r"(bar), "r"(c0), "r"(c1), "r"(c2), "r"(c3), "h"((uint16_t)3)
      : "memory");
}
__device__ __forceinline__ void tma_pf_2d(const CUtensorMap* m, int c0, int c1) {
  asm volatile("cp.async.bulk.prefetch.tensor.2d.L2.global [%0, {%1, %2}];\n" ::"l"((uint64_t)m), "r"(c0), "r"(c1) : "memory");
}
__device__ __forceinline__ void tma_pf_3d(const CUtensorMap* m, int c0, int c1, int c2) {
  asm volatile("cp.async.bulk.prefetch.tensor.3d.L2.global [%0, {%1, %2, %3}];\n" ::"l"((uint64_t)m), "r"(c0), "r"(c1), "r"(c2) : "memory");
}
__device__ __forceinline__ void tma_pf_4d(const CUtensorMap* m, int c0, int c1, int c2, int c3) {
  asm volatile("cp.async.bulk.prefetch.tensor.4d.L2.global [%0, {%1, %2, %3, %4}];\n" ::"l"((uint64_t)m), "r"(c0), "r"(c1), "r"(c2),
               "r"(c3)
               : "memory");
}
__device__ __forceinline__ void tma_store_2d(const CUtensorMap* m, uint32_t src, int c0, int c1) {
  asm volatile("cp.async.bulk.tensor.2d.global.shared::cta.bulk_group [%0, {%2, %3}], [%1];\n" ::"l"((uint64_t)m), "r"(src),
               "r"(c0), "r"(c1)
               : "memory");
}
__device__ __forceinline__ void prefetch_map(const CUtensorMap* m) {
  asm volatile("prefetch.tensormap [%0];\n" ::"l"((uint64_t)m) : "memory");
}
__device__ __forceinline__ void fence_async_smem() { asm volatile("fence.proxy.async.shared::cta;\n" ::: "memory"); }
__device__ __forceinline__ void stsm4(uint32_t addr, uint32_t a, uint32_t b, uint32_t c, uint32_t d) {
  asm volatile("stmatrix.sync.aligned.m8n8.x4.shared.b16 [%0], {%1, %2, %3, %4};\n" ::"r"(addr), "r"(a), "r"(b), "r"(c), "r"(d)
               : "memory");
}
__device__ __forceinline__ void ldsm4(uint32_t addr, uint32_t& a, uint32_t& b, uint32_t& c, uint32_t& d) {
  asm volatile("ldmatrix.sync.aligned.m8n8.x4.shared.b16 {%0, %1, %2, %3}, [%4];\n"
               : "=r"(a), "=r"(b), "=r"(c), "=r"(d)
               : "r"(addr)
               : "memory");
}
__device__ __forceinline__ float ex2(float x) {
  float y;
  asm("ex2.approx.ftz.f32 %0, %1;" : "=f"(y) : "f"(x));
  return y;
}
__device__ __forceinline__ uint32_t pack_bf16(float lo, float hi) {
  uint32_t r;
  asm("cvt.rn.bf16x2.f32 %0, %1, %2;" : "=r"(r) : "f"(hi), "f"(lo));
  return r;
}
__device__ __forceinline__ uint32_t pack_bf16_relu(float lo, float hi) {
  uint32_t r;
  asm("cvt.rn.relu.bf16x2.f32 %0, %1, %2;" : "=r"(r) : "f"(hi), "f"(lo));
  return r;
}
__device__ __forceinline__ float bf_lo(uint32_t v) {
  uint32_t r;
  asm("prmt.b32 %0, %1, 0, 0x1044;" : "=r"(r) : "r"(v));
  return __uint_as_float(r);
}
__device__ __forceinline__ float bf_hi(uint32_t v) { return __uint_as_float(v & 0xffff0000u); }
__device__ __forceinline__ float bf_round(float x) { return __bfloat162float(__float2bfloat16_rn(x)); }
__device__ __forceinline__ void named_sync(int id) { asm volatile("bar.sync %0, 128;\n" ::"r"(id) : "memory"); }
__device__ __forceinline__ void cluster_arrive() { asm volatile("barrier.cluster.arrive.relaxed.aligned;\n" ::: "memory"); }
__device__ __forceinline__ void cluster_wait() { asm volatile("barrier.cluster.wait.acquire.aligned;\n" ::: "memory"); }
#define TM(cond, idx)
#define TACC(acc, stmt) do { stmt; } while (0)
#define TPUT(cond, idx, v)

template <int TB>
__device__ __forceinline__ void wgmma_ss_n192(float (&d)[96], uint64_t da, uint64_t db, int scale_d) {
  asm volatile(
      "{\n.reg .pred p;\nsetp.ne.b32 p, %98, 0;\n"
      "wgmma.mma_async.sync.aligned.m64n192k16.f32.bf16.bf16 {"
      "%0, %1, %2, %3, %4, %5, %6, %7, %8, %9, %10, %11, %12, %13, %14, %15, "
      "%16, %17, %18, %19, %20, %21, %22, %23, %24, %25, %26, %27, %28, %29, %30, %31, "
      "%32, %33, %34, %35, %36, %37, %38, %39, %40, %41, %42, %43, %44, %45, %46, %47, "
      "%48, %49, %50, %51, %52, %53, %54, %55, %56, %57, %58, %59, %60, %61, %62, %63, "
      "%64, %65, %66, %67, %68, %69, %70, %71, %72, %73, %74, %75, %76, %77, %78, %79, "
      "%80, %81, %82, %83, %84, %85, %86, %87, %88, %89, %90, %91, %92, %93, %94, %95}, %96, %97, p, 1, 1, 0, %99;\n}\n"
      : "+f"(d[0]), "+f"(d[1]), "+f"(d[2]), "+f"(d[3]), "+f"(d[4]), "+f"(d[5]), "+f"(d[6]), "+f"(d[7]),
        "+f"(d[8]), "+f"(d[9]), "+f"(d[10]), "+f"(d[11]), "+f"(d[12]), "+f"(d[13]), "+f"(d[14]), "+f"(d[15]),
        "+f"(d[16]), "+f"(d[17]), "+f"(d[18]), "+f"(d[19]), "+f"(d[20]), "+f"(d[21]), "+f"(d[22]), "+f"(d[23]),
        "+f"(d[24]), "+f"(d[25]), "+f"(d[26]), "+f"(d[27]), "+f"(d[28]), "+f"(d[29]), "+f"(d[30]), "+f"(d[31]),
        "+f"(d[32]), "+f"(d[33]), "+f"(d[34]), "+f"(d[35]), "+f"(d[36]), "+f"(d[37]), "+f"(d[38]), "+f"(d[39]),
        "+f"(d[40]), "+f"(d[41]), "+f"(d[42]), "+f"(d[43]), "+f"(d[44]), "+f"(d[45]), "+f"(d[46]), "+f"(d[47]),
        "+f"(d[48]), "+f"(d[49]), "+f"(d[50]), "+f"(d[51]), "+f"(d[52]), "+f"(d[53]), "+f"(d[54]), "+f"(d[55]),
        "+f"(d[56]), "+f"(d[57]), "+f"(d[58]), "+f"(d[59]), "+f"(d[60]), "+f"(d[61]), "+f"(d[62]), "+f"(d[63]),
        "+f"(d[64]), "+f"(d[65]), "+f"(d[66]), "+f"(d[67]), "+f"(d[68]), "+f"(d[69]), "+f"(d[70]), "+f"(d[71]),
        "+f"(d[72]), "+f"(d[73]), "+f"(d[74]), "+f"(d[75]), "+f"(d[76]), "+f"(d[77]), "+f"(d[78]), "+f"(d[79]),
        "+f"(d[80]), "+f"(d[81]), "+f"(d[82]), "+f"(d[83]), "+f"(d[84]), "+f"(d[85]), "+f"(d[86]), "+f"(d[87]),
        "+f"(d[88]), "+f"(d[89]), "+f"(d[90]), "+f"(d[91]), "+f"(d[92]), "+f"(d[93]), "+f"(d[94]), "+f"(d[95])
      : "l"(da), "l"(db), "r"(scale_d), "n"(TB));
}
template <int TB>
__device__ __forceinline__ void wgmma_ss_n128(float (&d)[96], uint64_t da, uint64_t db, int scale_d) {
  asm volatile(
      "{\n.reg .pred p;\nsetp.ne.b32 p, %66, 0;\n"
      "wgmma.mma_async.sync.aligned.m64n128k16.f32.bf16.bf16 {"
      "%0, %1, %2, %3, %4, %5, %6, %7, %8, %9, %10, %11, %12, %13, %14, %15, "
      "%16, %17, %18, %19, %20, %21, %22, %23, %24, %25, %26, %27, %28, %29, %30, %31, "
      "%32, %33, %34, %35, %36, %37, %38, %39, %40, %41, %42, %43, %44, %45, %46, %47, "
      "%48, %49, %50, %51, %52, %53, %54, %55, %56, %57, %58, %59, %60, %61, %62, %63}, %64, %65, p, 1, 1, 0, %67;\n}\n"
      : "+f"(d[0]), "+f"(d[1]), "+f"(d[2]), "+f"(d[3]), "+f"(d[4]), "+f"(d[5]), "+f"(d[6]), "+f"(d[7]),
        "+f"(d[8]), "+f"(d[9]), "+f"(d[10]), "+f"(d[11]), "+f"(d[12]), "+f"(d[13]), "+f"(d[14]), "+f"(d[15]),
        "+f"(d[16]), "+f"(d[17]), "+f"(d[18]), "+f"(d[19]), "+f"(d[20]), "+f"(d[21]), "+f"(d[22]), "+f"(d[23]),
        "+f"(d[24]), "+f"(d[25]), "+f"(d[26]), "+f"(d[27]), "+f"(d[28]), "+f"(d[29]), "+f"(d[30]), "+f"(d[31]),
        "+f"(d[32]), "+f"(d[33]), "+f"(d[34]), "+f"(d[35]), "+f"(d[36]), "+f"(d[37]), "+f"(d[38]), "+f"(d[39]),
        "+f"(d[40]), "+f"(d[41]), "+f"(d[42]), "+f"(d[43]), "+f"(d[44]), "+f"(d[45]), "+f"(d[46]), "+f"(d[47]),
        "+f"(d[48]), "+f"(d[49]), "+f"(d[50]), "+f"(d[51]), "+f"(d[52]), "+f"(d[53]), "+f"(d[54]), "+f"(d[55]),
        "+f"(d[56]), "+f"(d[57]), "+f"(d[58]), "+f"(d[59]), "+f"(d[60]), "+f"(d[61]), "+f"(d[62]), "+f"(d[63])
      : "l"(da), "l"(db), "r"(scale_d), "n"(TB));
}
template <int TB>
__device__ __forceinline__ void wgmma_ss_n64(float (&d)[32], uint64_t da, uint64_t db, int scale_d) {
  asm volatile(
      "{\n.reg .pred p;\nsetp.ne.b32 p, %34, 0;\n"
      "wgmma.mma_async.sync.aligned.m64n64k16.f32.bf16.bf16 {"
      "%0, %1, %2, %3, %4, %5, %6, %7, %8, %9, %10, %11, %12, %13, %14, %15, "
      "%16, %17, %18, %19, %20, %21, %22, %23, %24, %25, %26, %27, %28, %29, %30, %31}, %32, %33, p, 1, 1, 0, %35;\n}\n"
      : "+f"(d[0]), "+f"(d[1]), "+f"(d[2]), "+f"(d[3]), "+f"(d[4]), "+f"(d[5]), "+f"(d[6]), "+f"(d[7]),
        "+f"(d[8]), "+f"(d[9]), "+f"(d[10]), "+f"(d[11]), "+f"(d[12]), "+f"(d[13]), "+f"(d[14]), "+f"(d[15]),
        "+f"(d[16]), "+f"(d[17]), "+f"(d[18]), "+f"(d[19]), "+f"(d[20]), "+f"(d[21]), "+f"(d[22]), "+f"(d[23]),
        "+f"(d[24]), "+f"(d[25]), "+f"(d[26]), "+f"(d[27]), "+f"(d[28]), "+f"(d[29]), "+f"(d[30]), "+f"(d[31])
      : "l"(da), "l"(db), "r"(scale_d), "n"(TB));
}
template <int TB>
__device__ __forceinline__ void wgmma_rs_n32(float (&d)[16], uint32_t a0, uint32_t a1, uint32_t a2, uint32_t a3,
                                             uint64_t db, int scale_d) {
  asm volatile(
      "{\n.reg .pred p;\nsetp.ne.b32 p, %21, 0;\n"
      "wgmma.mma_async.sync.aligned.m64n32k16.f32.bf16.bf16 {"
      "%0, %1, %2, %3, %4, %5, %6, %7, %8, %9, %10, %11, %12, %13, %14, %15}, {%16, %17, %18, %19}, %20, p, 1, 1, %22;\n}\n"
      : "+f"(d[0]), "+f"(d[1]), "+f"(d[2]), "+f"(d[3]), "+f"(d[4]), "+f"(d[5]), "+f"(d[6]), "+f"(d[7]),
        "+f"(d[8]), "+f"(d[9]), "+f"(d[10]), "+f"(d[11]), "+f"(d[12]), "+f"(d[13]), "+f"(d[14]), "+f"(d[15])
      : "r"(a0), "r"(a1), "r"(a2), "r"(a3), "l"(db), "r"(scale_d), "n"(TB));
}
template <int TB>
__device__ __forceinline__ void wgmma_rs_n40(float (&d)[20], uint32_t a0, uint32_t a1, uint32_t a2, uint32_t a3,
                                             uint64_t db, int scale_d) {
  asm volatile(
      "{\n.reg .pred p;\nsetp.ne.b32 p, %25, 0;\n"
      "wgmma.mma_async.sync.aligned.m64n40k16.f32.bf16.bf16 {"
      "%0, %1, %2, %3, %4, %5, %6, %7, %8, %9, %10, %11, %12, %13, %14, %15, "
      "%16, %17, %18, %19}, {%20, %21, %22, %23}, %24, p, 1, 1, %26;\n}\n"
      : "+f"(d[0]), "+f"(d[1]), "+f"(d[2]), "+f"(d[3]), "+f"(d[4]), "+f"(d[5]), "+f"(d[6]), "+f"(d[7]),
        "+f"(d[8]), "+f"(d[9]), "+f"(d[10]), "+f"(d[11]), "+f"(d[12]), "+f"(d[13]), "+f"(d[14]), "+f"(d[15]),
        "+f"(d[16]), "+f"(d[17]), "+f"(d[18]), "+f"(d[19])
      : "r"(a0), "r"(a1), "r"(a2), "r"(a3), "l"(db), "r"(scale_d), "n"(TB));
}

template <int N>
__device__ __forceinline__ void wgmma_gemm(float (&d)[96], uint64_t da, uint64_t db, int sc) {
  if constexpr (N == 192) wgmma_ss_n192<1>(d, da, db, sc);
  else wgmma_ss_n128<1>(d, da, db, sc);
}

__device__ __forceinline__ uint32_t next_slot(int pos, bool first_tile, uint32_t& r3) {
  const bool x = (pos & 3) == 2 && (first_tile || pos >= 6);
  const uint32_t s = x ? 3u : r3;
  r3 = x ? r3 : ((r3 == 2) ? 0u : r3 + 1);
  return s;
}
__device__ __forceinline__ bool out_kb_is_attn(int kb) { return (kb >= 40 && kb < 48) || kb >= 64; }

#define GWAIT(bar, par) do { if (!ready) mbar_wait(bar, par); } while (0)
struct GemmState {
  uint32_t lo0, bars, rel_addr;
  uint32_t phases, r3, s;
  bool rel_lane;
  uint32_t twait;
};
struct BFmt { uint32_t lbo, hi, k1, k2; };

template <int N>
__device__ __forceinline__ void mma_half(float (&d)[96], uint32_t a_lo, uint32_t a_hi, uint32_t a_k2, uint32_t b_lo, const BFmt b,
                                         int k, int sc) {
  wgmma_gemm<N>(d, mk_desc(a_lo + (k >> 1) * a_k2 + (k & 1) * 2, a_hi), mk_desc(b_lo + (k >> 1) * b.k2 + (k & 1) * b.k1, b.hi), sc);
}
template <int N>
__device__ __forceinline__ void tile_head(float (&d0)[96], GemmState& g, const BFmt b) {
  g.s = next_slot(0, false, g.r3);
  const bool ready = false;
  uint32_t& twait = g.twait;
  (void)twait;
  GWAIT(g.bars + (B_GFULL + g.s) * 8, (g.phases >> g.s) & 1);
  const uint32_t a_lo = g.lo0 + (1u << 16) + g.s * (kSlot >> 4), b_lo = g.lo0 + (16384 >> 4) + ((b.lbo >> 4) << 16) + g.s * (kSlot >> 4);
  fence_regs(d0);
  wgmma_fence();
#pragma unroll
  for (int k = 0; k < 4; k++) mma_half<N>(d0, a_lo, desc_hi(1024, 1), 64 >> 4, b_lo, b, k, k > 0);
  wgmma_commit();
}
template <int N, int NKB, int GD, bool OUTK>
__device__ __forceinline__ void tile_body(float (&d0)[96], float (&d1)[96], GemmState& g, const BFmt b) {
  const uint32_t a_c = g.lo0 + (1u << 16), b_c = g.lo0 + (16384 >> 4) + ((b.lbo >> 4) << 16);
  uint32_t s = g.s, rel, a_lo, b_lo;
  uint32_t a_hi = desc_hi(1024, 1), a_half = 8192 >> 4, a_k2 = 64 >> 4;
  uint32_t& twait = g.twait;
  (void)twait;
  bool ready;
  auto prepare = [&](int kb) {
    g.phases ^= 1u << s;
    rel = g.rel_addr + s * 8;
    s = next_slot(kb, false, g.r3);
    a_lo = a_c + s * (kSlot >> 4);
    b_lo = b_c + s * (kSlot >> 4);
    if (OUTK) {
      const bool at = out_kb_is_attn(kb);
      a_hi = at ? desc_hi(512, 2) : desc_hi(1024, 1);
      a_half = at ? 4096 >> 4 : 8192 >> 4;
      a_k2 = at ? 8192 >> 4 : 64 >> 4;
    }
    ready = mbar_test(g.bars + (B_GFULL + s) * 8, (g.phases >> s) & 1);
  };
  {
    const uint32_t ca = a_c + s * (kSlot >> 4) + (8192 >> 4), cb = b_c + s * (kSlot >> 4);
    fence_regs(d1);
    wgmma_fence();
#pragma unroll
    for (int k = 0; k < 4; k++) {
      wgmma_wait<GD>();
      mma_half<N>(d1, ca, desc_hi(1024, 1), 64 >> 4, cb, b, k, k > 0);
      wgmma_commit();
      if (k == 1) prepare(1);
    }
  }
#pragma unroll 1
  for (int kb = 1; kb < NKB - 1; kb++) {
    GWAIT(g.bars + (B_GFULL + s) * 8, (g.phases >> s) & 1);
    const uint32_t ca_lo = a_lo, cb_lo = b_lo, ca_hi = a_hi, ca_half = a_half, ca_k2 = a_k2, crel = rel;
    wgmma_fence();
#pragma unroll
    for (int k = 0; k < 4; k++) {
      wgmma_wait<GD>();
      mma_half<N>(d0, ca_lo, ca_hi, ca_k2, cb_lo, b, k, 1);
      wgmma_commit();
      if (2 * k == GD) mbar_arrive_cluster_if(crel, g.rel_lane);
      wgmma_wait<GD>();
      mma_half<N>(d1, ca_lo + ca_half, ca_hi, ca_k2, cb_lo, b, k, 1);
      wgmma_commit();
      if (2 * k + 1 == GD) mbar_arrive_cluster_if(crel, g.rel_lane);
      if (k == 2) prepare(kb + 1);
    }
  }
  GWAIT(g.bars + (B_GFULL + s) * 8, (g.phases >> s) & 1);
  g.phases ^= 1u << s;
  g.s = s;
  wgmma_fence();
#pragma unroll
  for (int k = 0; k < 4; k++) {
    wgmma_wait<GD>();
    mma_half<N>(d0, a_lo, a_hi, a_k2, b_lo, b, k, 1);
    wgmma_commit();
  }
#pragma unroll
  for (int k = 0; k < 4; k++) mma_half<N>(d1, a_lo + a_half, a_hi, a_k2, b_lo, b, k, 1);
  wgmma_commit();
  wgmma_wait<1>();
  fence_regs(d0);
}
__device__ __forceinline__ void tile_drain(float (&d1)[96], GemmState& g) {
  wgmma_wait<0>();
  fence_regs(d1);
  mbar_arrive_cluster_if(g.rel_addr + g.s * 8, g.rel_lane);
}

__device__ __forceinline__ void tile_first(float (&d0)[96], float (&d1)[96], float (&cs)[6], uint32_t sb, uint32_t rank,
                                           GemmState& g, const BFmt b) {
  const int lane = threadIdx.x & 31, w = (threadIdx.x >> 5) & 3;
  const uint32_t a_c = g.lo0 + (1u << 16), b_c = g.lo0 + (16384 >> 4) + ((b.lbo >> 4) << 16);
  uint32_t& twait = g.twait;
  (void)twait;
  bool ready = false;
  uint32_t prev = 0;
  const uint32_t cs_base = sb + 16384 + rank * 12288 + lane * 64 + ((w ^ ((lane >> 1) & 3)) << 4);
#pragma unroll 1
  for (int kb = 0; kb < 16; kb++) {
    const uint32_t s = (kb & 3) ^ ((kb >> 1) & 1);
    GWAIT(g.bars + (B_GFULL + s) * 8, (kb >> 2) & 1);
    const uint32_t a_lo = a_c + s * (kSlot >> 4), b_lo = b_c + s * (kSlot >> 4);
    wgmma_fence();
#pragma unroll
    for (int k = 0; k < 4; k++) mma_half<192>(d0, a_lo, desc_hi(1024, 1), 64 >> 4, b_lo, b, k, (k > 0) ? 1 : (kb > 0));
    wgmma_commit();
#pragma unroll
    for (int k = 0; k < 4; k++) mma_half<192>(d1, a_lo + (8192 >> 4), desc_hi(1024, 1), 64 >> 4, b_lo, b, k, (k > 0) ? 1 : (kb > 0));
    wgmma_commit();
    wgmma_wait<2>();
    mbar_arrive_cluster_if(g.rel_addr + prev * 8, g.rel_lane && kb > 0 && kb < 15);
    prev = s;
#pragma unroll
    for (int h = 0; h < 2; h++) {
      uint32_t bq[3][4];
#pragma unroll
      for (int i = 0; i < 3; i++)
        asm volatile("ldmatrix.sync.aligned.m8n8.x4.trans.shared.b16 {%0, %1, %2, %3}, [%4];\n"
                     : "=r"(bq[i][0]), "=r"(bq[i][1]), "=r"(bq[i][2]), "=r"(bq[i][3])
                     : "r"(cs_base + s * kSlot + (3 * h + i) * 2048)
                     : "memory");
#pragma unroll
      for (int i = 0; i < 3; i++)
        cs[3 * h + i] += ((bf_lo(bq[i][0]) + bf_hi(bq[i][0])) + (bf_lo(bq[i][1]) + bf_hi(bq[i][1]))) +
                         ((bf_lo(bq[i][2]) + bf_hi(bq[i][2])) + (bf_lo(bq[i][3]) + bf_hi(bq[i][3])));
    }
    asm volatile("" : "+f"(cs[0]), "+f"(cs[1]), "+f"(cs[2]), "+f"(cs[3]), "+f"(cs[4]), "+f"(cs[5])::"memory");
    ready = mbar_test(g.bars + (B_GFULL + (((kb + 1) & 3) ^ (((kb + 1) >> 1) & 1))) * 8, ((kb + 1) >> 2) & 1);
  }
  g.s = 2;
}

__device__ __forceinline__ void epi_publish(uint32_t bar, int lane) {
  fence_async_smem();
  __syncwarp();
  if (lane == 0) mbar_arrive(bar);
}
constexpr float kQScale = 0.17677669529663687f * 1.4426950408889634f;
template <int NJ, int NQ>
__device__ __forceinline__ void epi_qkv(const float (&d)[96], uint32_t base, uint32_t sw, uint32_t scol) {
#pragma unroll
  for (int jj = 0; jj < NJ; jj++) {
    const float f = jj < NQ ? kQScale : 1.f;
    stsm4(base + (jj >> 1) * 8192 + ((((jj & 1) * 2 + scol) ^ sw) << 4), pack_bf16(d[8 * jj] * f, d[8 * jj + 1] * f),
          pack_bf16(d[8 * jj + 2] * f, d[8 * jj + 3] * f), pack_bf16(d[8 * jj + 4] * f, d[8 * jj + 5] * f),
          pack_bf16(d[8 * jj + 6] * f, d[8 * jj + 7] * f));
  }
}
template <int R>
__device__ __forceinline__ void epi_qkv_ln(const float (&d)[96], uint32_t cs_addr, float2 s0, float2 s1, uint32_t base,
                                           uint32_t sw, uint32_t scol) {
  float c[4], cn[4];
  asm volatile("ld.shared.v2.f32 {%0, %1}, [%2];\n" : "=f"(cn[0]), "=f"(cn[1]) : "r"(cs_addr + R * 128));
  asm volatile("ld.shared.v2.f32 {%0, %1}, [%2];\n" : "=f"(cn[2]), "=f"(cn[3]) : "r"(cs_addr + R * 128 + 32));
#pragma unroll
  for (int q = 0; q < 6; q++) {
    const int jj = (q >> 1) * 4 + 2 * R + (q & 1), jn = ((q + 1) >> 1) * 4 + 2 * R + ((q + 1) & 1);
    const float f0 = jj < 4 ? kQScale * s0.y : s0.y, f1 = jj < 4 ? kQScale * s1.y : s1.y;
#pragma unroll
    for (int i = 0; i < 4; i++) c[i] = cn[i];
    if (q < 5) {
      asm volatile("ld.shared.v2.f32 {%0, %1}, [%2];\n" : "=f"(cn[0]), "=f"(cn[1]) : "r"(cs_addr + jn * 64));
      asm volatile("ld.shared.v2.f32 {%0, %1}, [%2];\n" : "=f"(cn[2]), "=f"(cn[3]) : "r"(cs_addr + jn * 64 + 32));
    }
    float v[8];
#pragma unroll
    for (int i = 0; i < 8; i++) {
      const float ci = c[(i >> 2) * 2 + (i & 1)];
      v[i] = (i & 2) ? fmaf(-s1.x, ci, d[8 * jj + i]) * f1 : fmaf(-s0.x, ci, d[8 * jj + i]) * f0;
    }
    stsm4(base + (jj >> 1) * 8192 + ((((jj & 1) * 2 + scol) ^ sw) << 4), pack_bf16(v[0], v[1]), pack_bf16(v[2], v[3]),
          pack_bf16(v[4], v[5]), pack_bf16(v[6], v[7]));
  }
}
template <int J0, int J1>
__device__ __forceinline__ void epi_relu(const float (&d)[96], uint32_t base, uint32_t sw, uint32_t scol) {
#pragma unroll
  for (int jj = J0; jj < J1; jj++)
    stsm4(base + ((jj - J0) >> 2) * 16384 + (((((jj - J0) & 3) * 2 + scol) ^ sw) << 4), pack_bf16_relu(d[8 * jj], d[8 * jj + 1]),
          pack_bf16_relu(d[8 * jj + 2], d[8 * jj + 3]), pack_bf16_relu(d[8 * jj + 4], d[8 * jj + 5]),
          pack_bf16_relu(d[8 * jj + 6], d[8 * jj + 7]));
}
template <int CH>
__device__ __forceinline__ void epi_out(const float (&d)[96], uint32_t base, uint32_t sw, uint32_t scol) {
  uint32_t x[4][4];
#pragma unroll
  for (int q = 0; q < 4; q++) ldsm4(base + CH * 16384 + (((q * 2 + scol) ^ sw) << 4), x[q][0], x[q][1], x[q][2], x[q][3]);
#pragma unroll
  for (int q = 0; q < 4; q++) {
    const int jj = 4 * CH + q;
    stsm4(base + CH * 16384 + (((q * 2 + scol) ^ sw) << 4), pack_bf16(d[8 * jj] + bf_lo(x[q][0]), d[8 * jj + 1] + bf_hi(x[q][0])),
          pack_bf16(d[8 * jj + 2] + bf_lo(x[q][1]), d[8 * jj + 3] + bf_hi(x[q][1])),
          pack_bf16(d[8 * jj + 4] + bf_lo(x[q][2]), d[8 * jj + 5] + bf_hi(x[q][2])),
          pack_bf16(d[8 * jj + 6] + bf_lo(x[q][3]), d[8 * jj + 7] + bf_hi(x[q][3])));
  }
}

__device__ __noinline__ void attn_exact(float* o_out, uint32_t q_smem_row_addr, const uint8_t* kv_head) {
  const int lane = threadIdx.x & 31, g = lane >> 2, t = lane & 3;
  uint32_t qa[2][4];
  {
    const int r = (lane & 7) + ((lane >> 3) & 1) * 8;
#pragma unroll
    for (int k = 0; k < 2; k++) {
      const int c16 = 2 * k + (lane >> 4);
      ldsm4(q_smem_row_addr + r * 64 + ((c16 ^ ((r >> 1) & 3)) << 4), qa[k][0], qa[k][1], qa[k][2], qa[k][3]);
    }
  }
  float o[16];
#pragma unroll
  for (int i = 0; i < 16; i++) o[i] = 0.f;
  float m0 = -INFINITY, m1 = -INFINITY, l0 = 0.f, l1 = 0.f;
#pragma unroll 1
  for (int kc = 0; kc < kS / 16; kc++) {
    const uint8_t* kt = kv_head + (kc >> 2) * 8192;
    const int k0 = (kc & 3) * 16;
    float s[2][4];
#pragma unroll
    for (int nb = 0; nb < 2; nb++) {
      s[nb][0] = s[nb][1] = s[nb][2] = s[nb][3] = 0.f;
      const int key = k0 + nb * 8 + g;
#pragma unroll
      for (int k = 0; k < 2; k++) {
        const uint32_t b0 = __ldcg((const uint32_t*)(kt + key * 64 + (((2 * k) ^ ((key >> 1) & 3)) << 4) + t * 4));
        const uint32_t b1 = __ldcg((const uint32_t*)(kt + key * 64 + (((2 * k + 1) ^ ((key >> 1) & 3)) << 4) + t * 4));
        asm volatile(
            "mma.sync.aligned.m16n8k16.row.col.f32.bf16.bf16.f32 {%0,%1,%2,%3}, {%4,%5,%6,%7}, {%8,%9}, {%0,%1,%2,%3};\n"
            : "+f"(s[nb][0]), "+f"(s[nb][1]), "+f"(s[nb][2]), "+f"(s[nb][3])
            : "r"(qa[k][0]), "r"(qa[k][1]), "r"(qa[k][2]), "r"(qa[k][3]), "r"(b0), "r"(b1));
      }
    }
    float x0 = fmaxf(fmaxf(s[0][0], s[0][1]), fmaxf(s[1][0], s[1][1]));
    float x1 = fmaxf(fmaxf(s[0][2], s[0][3]), fmaxf(s[1][2], s[1][3]));
    x0 = fmaxf(x0, __shfl_xor_sync(~0u, x0, 1)); x1 = fmaxf(x1, __shfl_xor_sync(~0u, x1, 1));
    x0 = fmaxf(x0, __shfl_xor_sync(~0u, x0, 2)); x1 = fmaxf(x1, __shfl_xor_sync(~0u, x1, 2));
    x0 = fmaxf(x0, m0); x1 = fmaxf(x1, m1);
    const float c0 = ex2(m0 - x0), c1 = ex2(m1 - x1);
    m0 = x0; m1 = x1;
    uint32_t p[4];
    {
      const float e00 = ex2(s[0][0] - m0), e01 = ex2(s[0][1] - m0), e02 = ex2(s[0][2] - m1), e03 = ex2(s[0][3] - m1);
      const float e10 = ex2(s[1][0] - m0), e11 = ex2(s[1][1] - m0), e12 = ex2(s[1][2] - m1), e13 = ex2(s[1][3] - m1);
      l0 = l0 * c0 + (e00 + e01 + e10 + e11);
      l1 = l1 * c1 + (e02 + e03 + e12 + e13);
      p[0] = pack_bf16(e00, e01); p[1] = pack_bf16(e02, e03); p[2] = pack_bf16(e10, e11); p[3] = pack_bf16(e12, e13);
    }
    const uint8_t* vt = kt + 4096;
#pragma unroll
    for (int nb = 0; nb < 4; nb++) {
      uint32_t hv[4];
#pragma unroll
      for (int i = 0; i < 4; i++) {
        const int key = k0 + 2 * t + (i & 1) + (i >> 1) * 8;
        hv[i] = __ldcg((const unsigned short*)(vt + key * 64 + ((nb ^ ((key >> 1) & 3)) << 4) + g * 2));
      }
      const uint32_t b0 = hv[0] | (hv[1] << 16), b1 = hv[2] | (hv[3] << 16);
      o[4 * nb] *= c0; o[4 * nb + 1] *= c0; o[4 * nb + 2] *= c1; o[4 * nb + 3] *= c1;
      asm volatile(
          "mma.sync.aligned.m16n8k16.row.col.f32.bf16.bf16.f32 {%0,%1,%2,%3}, {%4,%5,%6,%7}, {%8,%9}, {%0,%1,%2,%3};\n"
          : "+f"(o[4 * nb]), "+f"(o[4 * nb + 1]), "+f"(o[4 * nb + 2]), "+f"(o[4 * nb + 3])
          : "r"(p[0]), "r"(p[1]), "r"(p[2]), "r"(p[3]), "r"(b0), "r"(b1));
    }
  }
  l0 += __shfl_xor_sync(~0u, l0, 1); l1 += __shfl_xor_sync(~0u, l1, 1);
  l0 += __shfl_xor_sync(~0u, l0, 2); l1 += __shfl_xor_sync(~0u, l1, 2);
  const float i0 = 1.f / l0, i1 = 1.f / l1;
#pragma unroll
  for (int nb = 0; nb < 4; nb++) {
    o_out[4 * nb] = o[4 * nb] * i0; o_out[4 * nb + 1] = o[4 * nb + 1] * i0;
    o_out[4 * nb + 2] = o[4 * nb + 2] * i1; o_out[4 * nb + 3] = o[4 * nb + 3] * i1;
  }
}

struct Params {
  CUtensorMap wqkv, w1a, w1b, w2, wo, x, out;
  const __nv_bfloat16* xptr;
  const uint8_t *wqkv_p, *w1_p, *w2_p, *wo_p;
};

__global__ void __cluster_dims__(2, 1, 1) __launch_bounds__(kThreads, 1) fused_block_kernel(const __grid_constant__ Params P) {
  extern __shared__ __align__(1024) uint8_t smem_raw[];
  const uint32_t sb = (smem_u32(smem_raw) + 1023) & ~1023u;
  const uint32_t bars = sb + kBarOff;
  const int warp = __shfl_sync(~0u, threadIdx.x >> 5, 0);
  const int lane = threadIdx.x & 31;
  const uint32_t rank = blockIdx.x & 1;
  const int cl = blockIdx.x >> 1;
  const int c = ((cl & 1) << 2) | ((cl >> 3) & 3);
  const int m = (((cl & 6) | (cl >> 5)) << 1) + rank;
  TM(threadIdx.x == 0, 0);
  TPUT(threadIdx.x == 0, 60, clk32());

  if (threadIdx.x == 0) {
    for (int i = 0; i < 4; i++) { mbar_init(bars + (B_GFULL + i) * 8, 1); mbar_init(bars + (B_GEMPTY + i) * 8, 8); }
    for (int i = 0; i < (int)kNKv; i++) { mbar_init(bars + (B_KVFULL + i) * 8, 1); mbar_init(bars + (B_KVEMPTY + i) * 8, 16); }
    for (int i = 0; i < 2; i++) { mbar_init(bars + (B_QFULL + i) * 8, 1); mbar_init(bars + (B_QEMPTY + i) * 8, 1); mbar_init(bars + (B_GST + i) * 8, 4); }
    for (int i = 0; i < 4; i++) mbar_init(bars + (B_AST + i) * 8, 4);
    mbar_init(bars + B_STAT * 8, 1);
    mbar_init(bars + B_GST0 * 8, 4);
    for (int i = 0; i < 4; i++) mbar_init(bars + (B_OUT + i) * 8, 4);
    asm volatile("fence.mbarrier_init.release.cluster;\n" ::: "memory");
  }
  if (ONES && threadIdx.x >= 256) {
    asm volatile("st.shared.b32 [%0], %1;\n" ::"r"(sb + kOnesOff + (threadIdx.x - 256) * 4), "r"(0x3f803f80u) : "memory");
    fence_async_smem();
  }
  __syncthreads();
  cluster_arrive();

  if (warp < 4) {
    asm volatile("setmaxnreg.dec.sync.aligned.u32 32;\n");
    if (warp == 1 && lane == 0) { prefetch_map(&P.wqkv); prefetch_map(&P.w1a); prefetch_map(&P.w1b); prefetch_map(&P.w2); prefetch_map(&P.wo); }
    if (warp == 0 && lane == 0) {
      for (int kb = 0; kb < 4; kb++) {
        const int s = kb ^ (kb >> 1);
        mbar_expect_tx(bars + (B_GFULL + s) * 8, 16384 + 24576);
        tma_2d(sb + s * kSlot, &P.x, kb * 64, 128 * m, bars + (B_GFULL + s) * 8);
      }
    }
    if (warp == 2 && lane == 0) prefetch_map(&P.out);
    __syncwarp();
    cluster_wait();
    const bool lead = elect_one();
    {
      if (warp == 0) {
        uint32_t ph = 0xf, r3 = 0;
        const uint64_t pol = policy_evict_first();
        uint32_t full, dst;
        auto acquire = [&](int pos, bool first, uint32_t bytes) {
          const uint32_t s = next_slot(pos, first, r3);
          full = bars + s * 8;
          dst = sb + s * kSlot;
          const uint32_t par = (ph >> s) & 1;
          ph ^= 1u << s;
          mbar_wait_sleepy(full + B_GEMPTY * 8, par);
          if (bytes) if (lead) mbar_expect_tx(full, bytes);
        };
        const int kr = rank * 32;
        auto pfk = [&](int kb) { return ((kb & 8) + (m >> 1)) * 64 + kr; };
#pragma unroll 1
        for (int kb = 0; kb < 16; kb++) {
          acquire(kb, true, kb >= 4 ? 16384 + 24576 : 0);
          if (lead) tma_4d_mc(dst + 16384 + rank * 12288, &P.wqkv, 32 * c, kb * 64 + kr, 0, 0, full, pol);
          if (kb >= 4) if (lead) tma_2d(dst, &P.x, kb * 64, 128 * m, full);
          if (PFD && (kb & 7) == 4 && lead) tma_pf_4d(&P.wqkv, 32 * c, pfk(kb), 2, 0);
        }
        const uint8_t* xn = g_xn + (size_t)m * 16 * 16384;
#pragma unroll 1
        for (int kb = 0; kb < 16; kb++) {
          acquire(kb, false, 16384 + 24576);
          if (lead) tma_4d_mc(dst + 16384 + rank * 12288, &P.wqkv, 32 * c, kb * 64 + kr, 2, 0, full, pol);
          if (kb == 0) { flag_wait(&g_flags[(F_XN + m) * 32], 64); TM(lead, 1); }
          if (lead) bulk_g2s(dst, xn + kb * 16384, 16384, full);
          if (PFD && (kb & 7) == 4 && lead) tma_pf_3d(&P.w1a, 0, pfk(kb), 7 * c);
        }
#pragma unroll 1
        for (int kb = 0; kb < 16; kb++) {
          acquire(kb, false, 16384 + 24576);
          if (lead) bulk_g2s(dst, xn + kb * 16384, 16384, full);
          if (lead) tma_3d_mc(dst + 16384 + rank * 12288, &P.w1a, 0, kb * 64 + kr, 7 * c, full, pol);
          if (PFD && (kb & 7) == 4 && lead) tma_pf_3d(&P.w1b, 0, pfk(kb), 7 * c + 3);
        }
#pragma unroll 1
        for (int i = 0; i < 32; i++) {
          const int kb = i & 15;
          acquire(kb, false, 32768);
          if (lead) bulk_g2s(dst, xn + kb * 16384, 16384, full);
          if (lead) tma_3d_mc(dst + 16384 + rank * 8192, &P.w1b, 0, kb * 64 + kr, 7 * c + 3 + (i >> 4) * 2, full, pol);
          if (PFD && (kb & 7) == 4 && lead) {
            if (i < 16) tma_pf_3d(&P.w1b, 0, pfk(kb), 7 * c + 5);
            else tma_pf_3d(&P.w2, 0, (7 * (m >> 1) + (kb >> 3)) * 64 + kr, 2 * c);
          }
        }
        const uint8_t* hb = g_h + (size_t)m * 56 * 16384;
        const uint8_t* ob = g_o + (size_t)m * 32 * 8192;
        int pos = 0;
        auto out_h = [&](int n, int hk, int run, int skip, const unsigned* flag) {
          int cnt = 0;
#pragma unroll 1
          for (int i = 0; i < n; i++, pos++) {
            acquire(pos, false, 32768);
            if (lead) tma_3d_mc(dst + 16384 + rank * 8192, &P.w2, 0, hk * 64 + kr, 2 * c, full, pol);
            if (i == 0) flag_wait(flag, 16);
            if (lead) bulk_g2s(dst, hb + hk * 16384, 16384, full);
            hk++;
            if (++cnt == run) { cnt = 0; hk += skip; }
            if (PFD && (pos & 7) == 0 && pos < 40 && lead) tma_pf_3d(&P.w2, 0, (7 * (m >> 1) + 2 + (pos >> 3)) * 64 + kr, 2 * c);
            if (PFD && (pos & 15) == 4 && pos < 32 && lead) tma_pf_3d(&P.wo, 0, ((pos >> 1) - 2 + (m >> 1)) * 64 + kr, 2 * c);
          }
        };
        auto out_o = [&](int j0, int j1) {
#pragma unroll 1
          for (int j = j0; j < j1; j++, pos++) {
            acquire(pos, false, 32768);
            if (lead) tma_3d_mc(dst + 16384 + rank * 8192, &P.wo, 0, j * 64 + kr, 2 * c, full, pol);
            if ((j & 3) == 0) flag_wait(&g_flags[(F_O + m * 4 + (j >> 2)) * 32], 16);
            if (lead) bulk_g2s(dst, ob + j * 16384, 16384, full);
          }
        };
        out_h(24, 0, 3, 4, &g_flags[(F_H + m * 3 + 0) * 32]);
        out_h(16, 3, 2, 5, &g_flags[(F_H + m * 3 + 1) * 32]);
        out_o(0, 8);
        out_h(16, 5, 2, 5, &g_flags[(F_H + m * 3 + 2) * 32]);
        if (lead) { tma_pf_2d(&P.x, 128 * c, 128 * m); tma_pf_2d(&P.x, 128 * c + 64, 128 * m); }
        out_o(8, 16);
        if (lead) {
          mbar_expect_tx(bars + B_STAT * 8, 32768);
          tma_2d(sb + kKvOff, &P.x, 128 * c, 128 * m, bars + B_STAT * 8);
          tma_2d(sb + kKvOff + 16384, &P.x, 128 * c + 64, 128 * m, bars + B_STAT * 8);
        }
      } else if (warp == 1) {
        flag_wait(&g_flags[(F_XN + m) * 32], 64);
        if (lead) mbar_expect_tx(bars + B_STAT * 8, 1024 + 1536);
        if (lead) bulk_g2s(sb + kQOff + 8192, g_stat + m * 128, 1024, bars + B_STAT * 8);
        uint32_t ph = 1, full = bars + B_KVFULL * 8, dst = sb + kKvOff + rank * 4096;
        const uint8_t* src = g_kv + (size_t)c * 32 * 8192 + rank * 4096;
#pragma unroll 1
        for (int g = 0; g <= 128; g++) {
          if ((g & 31) == 0 && g < 128) {
            const int u = g >> 5, head = 8 * u + c;
            flag_wait(&g_flags[(F_KV + head) * 32], 32);
            TM(lead, 2 + u);
            if (u >= 2) mbar_wait_sleepy(bars + (B_QEMPTY + (u & 1)) * 8, 0);
            if (lead) mbar_expect_tx(bars + (B_QFULL + (u & 1)) * 8, 8192);
            if (lead) bulk_g2s(sb + kQOff + (u & 1) * 8192, g_q + ((size_t)head * kS + m * 128) * 64, 8192, bars + (B_QFULL + (u & 1)) * 8);
          }
          mbar_wait_sleepy(full + (B_KVEMPTY - B_KVFULL) * 8, ph);
          if (lead) mbar_expect_tx(full, 8192);
          if (lead) bulk_g2s_mc(dst, src, 4096, full);
          const int t = g + 1 - (int)rank;
          if (t > 0 && t < 128) src += (t & 31) ? 8192 : 8192 + 7 * 32 * 8192;
          full += 8;
          dst += 8192;
          if (full == bars + (B_KVFULL + kNKv) * 8) { full -= kNKv * 8; dst -= kNKv * 8192; ph ^= 1; }
        }
      } else if (lane != 0) {
      } else if (warp == 2) {
        const uint32_t st = sb + kStageOff;
        auto store_head = [&](int head, int r, int h) {
          uint8_t* kv = g_kv + ((size_t)head * 32 + 2 * m + h) * 8192;
          bulk_s2g(kv, st + (2 + r) * 8192 + h * 4096, 4096);
          bulk_s2g(kv + 4096, st + (4 + r) * 8192 + h * 4096, 4096);
          bulk_s2g(g_q + ((size_t)head * kS + m * 128 + h * 64) * 64, st + r * 8192 + h * 4096, 4096);
        };
        mbar_wait_sleepy(bars + B_GST0 * 8, 0);
        store_head(c, 0, 0);
        mbar_wait_sleepy(bars + B_GST * 8, 0);
        store_head(c, 0, 1);
        bulk_commit();
        bulk_wait_all();
        flag_add(&g_flags[(F_KV + c) * 32], 2);
        TM(true, 52);
        mbar_wait_sleepy(bars + (B_GST + 1) * 8, 0);
        store_head(8 + c, 1, 0);
        store_head(8 + c, 1, 1);
        bulk_commit();
        bulk_wait_read();
        mbar_arrive_cta(bars + (B_GEMPTY + 3) * 8, 0, 4);
        mbar_arrive_cta(bars + (B_GEMPTY + 3) * 8, 1, 4);
        bulk_wait_all();
        flag_add(&g_flags[(F_KV + 8 + c) * 32], 2);
        TM(true, 8);
#pragma unroll 1
        for (int t = 1; t < 5; t++) {
#pragma unroll 1
          for (int h = 0; h < 2; h++) {
            mbar_wait_sleepy(bars + (B_GST + h) * 8, t & 1);
            if (t < 2) {
              store_head(16 + c, 0, h);
              store_head(24 + c, 1, h);
            } else {
              const int a0 = t == 2 ? 7 * c : 7 * c + 2 * t - 3, na = t == 2 ? 3 : 2;
              for (int a = 0; a < na; a++)
                bulk_s2g(g_h + ((size_t)m * 56 + a0 + a) * 16384 + h * 8192, st + a * 16384 + h * 8192, 8192);
            }
            bulk_commit();
          }
          bulk_wait_read();
          mbar_arrive_cta(bars + (B_GEMPTY + 3) * 8, 0, 4);
          mbar_arrive_cta(bars + (B_GEMPTY + 3) * 8, 1, 4);
          bulk_wait_all();
          if (t < 2) {
            flag_add(&g_flags[(F_KV + 16 * t + c) * 32], 2);
            flag_add(&g_flags[(F_KV + 16 * t + 8 + c) * 32], 2);
          } else {
            flag_add(&g_flags[(F_H + m * 3 + t - 2) * 32], 2);
          }
          TM(true, 8 + t);
        }
#pragma unroll 1
        for (int i = 0; i < 4; i++) {
          mbar_wait(bars + (B_OUT + i) * 8, 0);
          tma_store_2d(&P.out, sb + kKvOff + (i & 1) * 16384 + (i >> 1) * 8192, 128 * c + 64 * (i & 1), 128 * m + 64 * (i >> 1));
          bulk_commit();
        }
        bulk_wait_all();
        TM(true, 13);
      } else {
        if (PREF & 1) {
          for (int i = 0; i < 6; i++) l2_prefetch(P.wqkv_p + (size_t)blockIdx.x * 49152 + i * 8192, 8192);
          for (int i = 0; i < 7; i++) l2_prefetch(P.w1_p + (size_t)blockIdx.x * 57344 + i * 8192, 8192);
        }
#pragma unroll 1
        for (int u = 0; u < 4; u++) {
          for (int w = 0; w < 2; w++) {
            mbar_wait_sleepy(bars + (B_AST + w * 2 + (u & 1)) * 8, u >> 1);
            bulk_s2g(g_o + ((size_t)m * 32 + 8 * u + c) * 8192 + w * 4096, sb + kQOff + (u & 1) * 8192 + w * 4096, 4096);
            bulk_commit();
          }
          bulk_wait_read();
          mbar_arrive(bars + (B_QEMPTY + (u & 1)) * 8);
          bulk_wait_all();
          flag_add(&g_flags[(F_O + m * 4 + u) * 32], 2);
          TM(true, 14 + u);
          if ((PREF & 2) && u == 0) {
            for (int i = 0; i < 7; i++) l2_prefetch(P.w2_p + (size_t)blockIdx.x * 57344 + i * 8192, 8192);
            for (int i = 0; i < 2; i++) l2_prefetch(P.wo_p + (size_t)blockIdx.x * 16384 + i * 8192, 8192);
          }
        }
      }
    }
    __syncwarp();
  } else if (warp < 8) {
    asm volatile("setmaxnreg.inc.sync.aligned.u32 240;\n");
    cluster_wait();
    const int w = warp & 3;
    GemmState g;
    g.lo0 = (sb & 0x3FFFF) >> 4;
    asm volatile("" : "+r"(g.lo0));
    g.lo0 = __shfl_sync(~0u, g.lo0, 0);
    g.bars = bars;
    g.rel_addr = mapa(bars + B_GEMPTY * 8, lane & 1);
    g.rel_lane = lane < 2;
    g.phases = 0; g.r3 = 0; g.s = 0; g.twait = 0;
    const BFmt fq = {2048, desc_hi(512, 2), 1024 >> 4, 12288 >> 4};
    const BFmt f192 = {4096, desc_hi(1024, 1), 2048 >> 4, 12288 >> 4};
    const BFmt f128 = {4096, desc_hi(1024, 1), 2048 >> 4, 8192 >> 4};
    const uint32_t srow = w * 16 + (lane & 7) + ((lane >> 3) & 1) * 8, scol = lane >> 4;
    const uint32_t st = sb + kStageOff;
    const uint32_t gst0 = bars + B_GST * 8, gst1 = gst0 + 8;
    const uint32_t b64 = st + srow * 64, sw64 = (srow >> 1) & 3, b128 = srow * 128, sw128 = srow & 7;
    float d0[96], d1[96], cs[6] = {0.f, 0.f, 0.f, 0.f, 0.f, 0.f};
#pragma unroll
    for (int i = 0; i < 96; i++) { d0[i] = 0.f; d1[i] = 0.f; }
    tile_first(d0, d1, cs, sb, rank, g, fq);
    const uint32_t csb = sb + kQOff + 8192 + 1024;
    {
      const uint32_t cs_dst = mapa(csb + rank * 768 + (8 * w + (lane >> 2)) * 4, lane & 1), cs_bar = mapa(bars + B_STAT * 8, lane & 1);
#pragma unroll
      for (int i = 0; i < 6; i++) cs[i] += __shfl_xor_sync(~0u, cs[i], 1);
#pragma unroll
      for (int i = 0; i < 6; i++) cs[i] += __shfl_xor_sync(~0u, cs[i], 2);
      if ((lane & 3) < 2) {
#pragma unroll
        for (int i = 0; i < 6; i++)
          asm volatile("st.async.weak.shared::cluster.mbarrier::complete_tx::bytes.b32 [%0], %1, [%2];\n" ::"r"(cs_dst + i * 128),
                       "r"(__float_as_uint(cs[i])), "r"(cs_bar)
                       : "memory");
      }
    }
    mbar_wait(bars + B_STAT * 8, 0);
    if (threadIdx.x < 128 + 96) {
      const uint32_t a = csb + (threadIdx.x - 128) * 8;
      float x0, x1, y0, y1;
      asm volatile("ld.shared.v2.f32 {%0, %1}, [%2];\n" : "=f"(x0), "=f"(x1) : "r"(a));
      asm volatile("ld.shared.v2.f32 {%0, %1}, [%2];\n" : "=f"(y0), "=f"(y1) : "r"(a + 768));
      asm volatile("st.shared.v2.f32 [%0], {%1, %2};\n" ::"r"(a), "f"(x0 + y0), "f"(x1 + y1) : "memory");
    }
    float2 sv[4];
#pragma unroll
    for (int i = 0; i < 4; i++)
      asm volatile("ld.shared.v2.f32 {%0, %1}, [%2];\n" : "=f"(sv[i].x), "=f"(sv[i].y)
                   : "r"(sb + kQOff + 8192 + ((i >> 1) * 64 + w * 16 + (lane >> 2) + (i & 1) * 8) * 8));
    wgmma_wait<1>();
    fence_regs(d0);
    TM(threadIdx.x == 128, 20); TPUT(threadIdx.x == 128, 41, clk32());
    named_sync(1);
    epi_qkv_ln<0>(d0, csb + (lane & 3) * 8, sv[0], sv[1], b64, sw64, scol);
    epi_publish(bars + B_GST0 * 8, lane);
    epi_qkv_ln<1>(d0, csb + (lane & 3) * 8, sv[0], sv[1], b64, sw64, scol);
    tile_drain(d1, g);
    tile_head<192>(d0, g, fq);
    epi_qkv_ln<0>(d1, csb + (lane & 3) * 8, sv[2], sv[3], b64 + 4096, sw64, scol);
    epi_publish(gst0, lane);
    epi_qkv_ln<1>(d1, csb + (lane & 3) * 8, sv[2], sv[3], b64 + 4096, sw64, scol);
    epi_publish(gst1, lane);
    TM(threadIdx.x == 128, 26);
    tile_body<192, 16, GD192, false>(d0, d1, g, fq);
    TM(threadIdx.x == 128, 21);
    named_sync(1);
    epi_qkv<12, 4>(d0, b64, sw64, scol);
    epi_publish(gst0, lane);
    tile_drain(d1, g);
    tile_head<192>(d0, g, f192);
    epi_qkv<12, 4>(d1, b64 + 4096, sw64, scol);
    epi_publish(gst1, lane);
    TM(threadIdx.x == 128, 27);
    tile_body<192, 16, GD192, false>(d0, d1, g, f192);
    TM(threadIdx.x == 128, 22);
    named_sync(1);
    epi_relu<0, 12>(d0, st + b128, sw128, scol);
    epi_publish(gst0, lane);
    tile_drain(d1, g);
    tile_head<128>(d0, g, f128);
    epi_relu<0, 12>(d1, st + 8192 + b128, sw128, scol);
    epi_publish(gst1, lane);
#pragma unroll
    for (int t = 3; t < 5; t++) {
      tile_body<128, 16, GD128, false>(d0, d1, g, f128);
      TM(threadIdx.x == 128, 20 + t); TPUT(threadIdx.x == 128 && t == 4, 63, clk32());
      named_sync(1);
      epi_relu<0, 8>(d0, st + b128, sw128, scol);
      epi_publish(gst0, lane);
      tile_drain(d1, g);
      tile_head<128>(d0, g, f128);
      epi_relu<0, 8>(d1, st + 8192 + b128, sw128, scol);
      epi_publish(gst1, lane);
    }
    tile_body<128, 72, GDOUT, true>(d0, d1, g, f128);
    TM(threadIdx.x == 128, 25); TPUT(threadIdx.x == 128, 62, clk32());
    mbar_wait(bars + B_STAT * 8, 1);
    epi_out<0>(d0, sb + kKvOff + b128, sw128, scol);
    epi_publish(bars + (B_OUT + 0) * 8, lane);
    epi_out<1>(d0, sb + kKvOff + b128, sw128, scol);
    epi_publish(bars + (B_OUT + 1) * 8, lane);
    wgmma_wait<0>();
    fence_regs(d1);
    epi_out<0>(d1, sb + kKvOff + 8192 + b128, sw128, scol);
    epi_publish(bars + (B_OUT + 2) * 8, lane);
    epi_out<1>(d1, sb + kKvOff + 8192 + b128, sw128, scol);
    epi_publish(bars + (B_OUT + 3) * 8, lane);
  } else {
    asm volatile("setmaxnreg.dec.sync.aligned.u32 120;\n");
    {
      const int r0 = c * 16 + (warp - 8) * 2;
      const uint32_t lnbuf = sb + kKvOff + (warp - 8) * 4096;
      const uint32_t statbuf = sb + kKvOff + 32768 + (warp - 8) * 16;
      uint4 v[2][4];
#pragma unroll
      for (int i = 0; i < 2; i++)
#pragma unroll
        for (int j = 0; j < 4; j++)
          v[i][j] = __ldg(reinterpret_cast<const uint4*>(P.xptr + (size_t)(m * 128 + r0 + i) * kD) + lane + 32 * j);
      TM(threadIdx.x == 256, 56);
#pragma unroll
      for (int i = 0; i < 2; i++) {
        float f[32];
#pragma unroll
        for (int j = 0; j < 4; j++) {
          f[8 * j] = bf_lo(v[i][j].x); f[8 * j + 1] = bf_hi(v[i][j].x); f[8 * j + 2] = bf_lo(v[i][j].y); f[8 * j + 3] = bf_hi(v[i][j].y);
          f[8 * j + 4] = bf_lo(v[i][j].z); f[8 * j + 5] = bf_hi(v[i][j].z); f[8 * j + 6] = bf_lo(v[i][j].w); f[8 * j + 7] = bf_hi(v[i][j].w);
        }
        float sum = 0.f;
#pragma unroll
        for (int j = 0; j < 32; j++) sum += f[j];
#pragma unroll
        for (int o = 16; o; o >>= 1) sum += __shfl_xor_sync(~0u, sum, o);
        const float mean = sum * (1.f / kD);
        TM(threadIdx.x == 256 && i == 0 && mean != 123.f, 57);
        float sq = 0.f;
#pragma unroll
        for (int j = 0; j < 32; j++) { const float dlt = f[j] - mean; sq = fmaf(dlt, dlt, sq); }
#pragma unroll
        for (int o = 16; o; o >>= 1) sq += __shfl_xor_sync(~0u, sq, o);
        const float mb = bf_round(mean);
        const float den = bf_round(sqrtf(bf_round(bf_round(sq * (1.f / kD)) + 1e-5f)));
        const float inv = 1.f / den;
        const int r = r0 + i;
        if (lane == 0) asm volatile("st.shared.v2.f32 [%0], {%1, %2};\n" ::"r"(statbuf + i * 8), "f"(mb), "f"(inv) : "memory");
#pragma unroll
        for (int j = 0; j < 4; j++) {
          uint4 o;
          uint32_t dd[4];
#pragma unroll
          for (int e = 0; e < 4; e++) {
            const uint32_t t = pack_bf16(f[8 * j + 2 * e] - mb, f[8 * j + 2 * e + 1] - mb);
            dd[e] = pack_bf16(bf_lo(t) * inv, bf_hi(t) * inv);
          }
          o.x = dd[0]; o.y = dd[1]; o.z = dd[2]; o.w = dd[3];
          const int ch = lane + 32 * j;
          asm volatile("st.shared.v4.b32 [%0], {%1, %2, %3, %4};\n" ::"r"(lnbuf + (ch >> 3) * 256 + i * 128 + (((ch & 7) ^ (r & 7)) << 4)),
                       "r"(o.x), "r"(o.y), "r"(o.z), "r"(o.w)
                       : "memory");
        }
      }
      TM(threadIdx.x == 256, 58);
      fence_async_smem();
      __syncwarp();
      if (lane < 17) {
        if (lane < 16) bulk_s2g(g_xn + ((size_t)(m * 16 + lane) * 128 + r0) * 128, lnbuf + lane * 256, 256);
        else bulk_s2g(g_stat + m * 128 + r0, statbuf, 16);
        bulk_commit();
        bulk_wait_all();
      }
      __syncwarp();
      if (lane == 0) flag_add(&g_flags[(F_XN + m) * 32], 1);
      TM(threadIdx.x == 256, 59);
    }
    cluster_wait();
    const int aw = (warp - 8) >> 2, w = warp & 3;
    const bool rel_lane = lane < 2;
    const uint32_t rel_addr = mapa(bars + B_KVEMPTY * 8, lane & 1);
    constexpr int NO = ONES ? 20 : 16;
    float s[32], o[NO];
    uint32_t pa[16], pb[16];
#pragma unroll
    for (int i = 0; i < 16; i++) { pa[i] = 0u; pb[i] = 0u; }
#pragma unroll
    for (int i = 0; i < NO; i++) o[i] = 0.f;
#pragma unroll
    for (int i = 0; i < 32; i++) s[i] = 0.f;
    float l0 = 0.f, l1 = 0.f, lp0 = 0.f, lp1 = 0.f;
    const uint32_t hi64 = desc_hi(512, 2);
    const uint32_t kv_lo0 = desc_lo(sb + kKvOff, 16);
    uint32_t st = 0, ph = 0, q_lo = 0;
    uint32_t rel_prev = rel_addr;
    bool ready = false, pend = false;
    const uint32_t v_lo0 = desc_lo(sb + kKvOff + 4096, kOnesOff - kKvOff - 4096);
    auto issue_pv = [&](uint32_t (&p)[16], int acc) {
      const uint32_t v_lo = v_lo0 + st * (512u - (512u << 16));
      wgmma_rs_n40<1>(o, p[0], p[1], p[2], p[3], mk_desc(v_lo, hi64), acc);
      wgmma_rs_n40<1>(o, p[4], p[5], p[6], p[7], mk_desc(v_lo + (64u - (64u << 16)), hi64), 1);
      wgmma_rs_n40<1>(o, p[8], p[9], p[10], p[11], mk_desc(v_lo + (128u - (128u << 16)), hi64), 1);
      wgmma_rs_n40<1>(o, p[12], p[13], p[14], p[15], mk_desc(v_lo + (192u - (192u << 16)), hi64), 1);
    };
    auto issue_qk = [&]() {
      const uint32_t k_lo = kv_lo0 + st * 512;
      wgmma_ss_n64<0>(s, mk_desc(q_lo, hi64), mk_desc(k_lo, hi64), 0);
      wgmma_ss_n64<0>(s, mk_desc(q_lo + 2, hi64), mk_desc(k_lo + 2, hi64), 1);
    };
    auto softmax_tile = [&](uint32_t (&p)[16]) {
#pragma unroll
      for (int i = 0; i < 8; i++) {
        const float e0 = ex2(s[4 * i]), e1 = ex2(s[4 * i + 1]), e2 = ex2(s[4 * i + 2]), e3 = ex2(s[4 * i + 3]);
        if (!ONES) { l0 += e0 + e1; l1 += e2 + e3; }
        p[2 * i] = pack_bf16(e0, e1); p[2 * i + 1] = pack_bf16(e2, e3);
      }
    };
    auto advance = [&]() {
      rel_prev = rel_addr + st * 8;
      if (++st == kNKv) { st = 0; ph ^= 1; }
      ready = mbar_test(bars + (B_KVFULL + st) * 8, ph);
    };
    auto finish = [&](int u) {
      const uint32_t ob = sb + kQOff + (u & 1) * 8192 + aw * 4096;
      const float t0 = o[16], t1 = o[18];
      bool ok = t0 >= 8.271806e-25f && t0 <= 1.2676506e30f && t1 >= 8.271806e-25f && t1 <= 1.2676506e30f;
#pragma unroll
      for (int i = 0; i < 16; i++) ok = ok && (fabsf(o[i]) <= 3.0e38f);
      const float i0 = 1.f / t0, i1 = 1.f / t1;
      uint32_t r[8];
#pragma unroll
      for (int i = 0; i < 4; i++) {
        r[2 * i] = pack_bf16(o[4 * i] * i0, o[4 * i + 1] * i0);
        r[2 * i + 1] = pack_bf16(o[4 * i + 2] * i1, o[4 * i + 3] * i1);
      }
      if (__any_sync(~0u, !ok)) {
        float e[16];
        attn_exact(e, ob + w * 1024, g_kv + (size_t)(8 * u + c) * 32 * 8192);
#pragma unroll
        for (int i = 0; i < 8; i++) r[i] = pack_bf16(e[2 * i], e[2 * i + 1]);
      }
      __syncwarp();
      const uint32_t srow = w * 16 + (lane & 7) + ((lane >> 3) & 1) * 8, scol = lane >> 4;
      const uint32_t base = ob + srow * 64, sw = (srow >> 1) & 3;
      stsm4(base + ((scol ^ sw) << 4), r[0], r[1], r[2], r[3]);
      stsm4(base + (((2 + scol) ^ sw) << 4), r[4], r[5], r[6], r[7]);
      epi_publish(bars + (B_AST + aw * 2 + (u & 1)) * 8, lane);
      TM(threadIdx.x == 256, 31 + u);
      TPUT(threadIdx.x == 256, 47 + u, clk32());
    };
    auto issue = [&](uint32_t (&pin)[16], uint32_t (&pout)[16], int acc) {
      fence_regs(s); fence_regs(o); fence_regs(pin); fence_regs(pout);
      wgmma_fence();
      issue_qk();
      wgmma_commit();
      issue_pv(pin, acc);
      wgmma_commit();
      mbar_arrive_cluster_if(rel_prev, rel_lane && pend);
      pend = true;
      wgmma_wait<1>();
      fence_regs(s);
      advance();
    };
    mbar_wait(bars + B_KVFULL * 8, 0);
#pragma unroll 1
    for (int it = 0; it <= 64; it++) {
      const bool bnd = (it & 15) == 0;
      const int u = it >> 4;
      if (bnd) {
        q_lo = desc_lo(sb + kQOff + (u & 1) * 8192 + aw * 4096, 16);
        if (u < 4) mbar_wait(bars + (B_QFULL + (u & 1)) * 8, u >> 1);
        lp0 = l0; lp1 = l1; l0 = 0.f; l1 = 0.f;
      }
      issue(pb, pa, 1);
      softmax_tile(pa);
      if (!ready && it < 64) mbar_wait(bars + (B_KVFULL + st) * 8, ph);
      wgmma_wait<0>();
      if (bnd) {
        fence_regs(o);
        if (it > 0) finish(u - 1);
        if (it == 64) break;
      }
      issue(pa, pb, !bnd);
      softmax_tile(pb);
      if (!ready) mbar_wait(bars + (B_KVFULL + st) * 8, ph);
      wgmma_wait<0>();
    }
  }

  cluster_arrive();
  cluster_wait();
  if (threadIdx.x == 0) {
    TM(true, 40);
    TPUT(true, 61, clk32());
    asm volatile("fence.acq_rel.gpu;\n" ::: "memory");
    const unsigned old = atomicAdd(&g_flags[F_DONE * 32], 1u);
    if (old == kCtas - 1) {
      asm volatile("fence.acq_rel.gpu;\n" ::: "memory");
      for (int i = 0; i < F_COUNT; i++) g_flags[i * 32] = 0u;
    }
  }
}

typedef CUresult (*EncodeFn)(CUtensorMap*, CUtensorMapDataType, cuuint32_t, void*, const cuuint64_t*, const cuuint64_t*,
                             const cuuint32_t*, const cuuint32_t*, CUtensorMapInterleave, CUtensorMapSwizzle,
                             CUtensorMapL2promotion, CUtensorMapFloatOOBfill);

void encode(EncodeFn fn, CUtensorMap* map, const void* base, int rank, const cuuint64_t* dims, const cuuint64_t* strides,
            const cuuint32_t* box, CUtensorMapSwizzle sw) {
  const cuuint32_t es[5] = {1, 1, 1, 1, 1};
  fn(map, CU_TENSOR_MAP_DATA_TYPE_BFLOAT16, rank, const_cast<void*>(base), dims, strides, box, es,
     CU_TENSOR_MAP_INTERLEAVE_NONE, sw, CU_TENSOR_MAP_L2_PROMOTION_L2_256B, CU_TENSOR_MAP_FLOAT_OOB_FILL_NONE);
}

}

extern "C" void kernel_launch(void* const* d_in, const int* in_sizes, int n_in, void* d_out, int out_size) {
  (void)in_sizes; (void)n_in; (void)out_size;
  static Params P;
  static const void* key[6] = {nullptr, nullptr, nullptr, nullptr, nullptr, nullptr};
  const void* cur[6] = {d_in[0], d_in[1], d_in[2], d_in[4], d_in[5], d_out};
  bool same = true;
  for (int i = 0; i < 6; i++) same = same && key[i] == cur[i];
  if (!same) {
    void* fn = nullptr;
    cudaDriverEntryPointQueryResult q;
    cudaGetDriverEntryPoint("cuTensorMapEncodeTiled", &fn, cudaEnableDefault, &q);
    EncodeFn enc = (EncodeFn)fn;
    {
      const cuuint64_t d[4] = {256, 1024, 4, 3}, s[3] = {6144, 512, 2048};
      const cuuint32_t b[4] = {32, 32, 2, 3};
      encode(enc, &P.wqkv, d_in[1], 4, d, s, b, CU_TENSOR_MAP_SWIZZLE_64B);
    }
    {
      const cuuint64_t d[3] = {64, 1024, 56}, s[2] = {kDff * 2, 128};
      const cuuint32_t b3[3] = {64, 32, 3}, b2[3] = {64, 32, 2};
      encode(enc, &P.w1a, d_in[4], 3, d, s, b3, CU_TENSOR_MAP_SWIZZLE_128B);
      encode(enc, &P.w1b, d_in[4], 3, d, s, b2, CU_TENSOR_MAP_SWIZZLE_128B);
    }
    {
      const cuuint64_t d2[3] = {64, kDff, 16}, d1[3] = {64, kD, 16}, s[2] = {kD * 2, 128};
      const cuuint32_t b[3] = {64, 32, 2};
      encode(enc, &P.w2, d_in[5], 3, d2, s, b, CU_TENSOR_MAP_SWIZZLE_128B);
      encode(enc, &P.wo, d_in[2], 3, d1, s, b, CU_TENSOR_MAP_SWIZZLE_128B);
    }
    {
      const cuuint64_t d[2] = {kD, kS}, s[1] = {kD * 2};
      const cuuint32_t bx[2] = {64, 128}, bo[2] = {64, 64};
      encode(enc, &P.x, d_in[0], 2, d, s, bx, CU_TENSOR_MAP_SWIZZLE_128B);
      encode(enc, &P.out, d_out, 2, d, s, bo, CU_TENSOR_MAP_SWIZZLE_128B);
    }
    P.xptr = (const __nv_bfloat16*)d_in[0];
    P.wqkv_p = (const uint8_t*)d_in[1];
    P.wo_p = (const uint8_t*)d_in[2];
    P.w1_p = (const uint8_t*)d_in[4];
    P.w2_p = (const uint8_t*)d_in[5];
    cudaFuncSetAttribute(fused_block_kernel, cudaFuncAttributeMaxDynamicSharedMemorySize, kSmemBytes);
    for (int i = 0; i < 6; i++) key[i] = cur[i];
  }
  fused_block_kernel<<<kCtas, kThreads, kSmemBytes>>>(P);
}
```

```cpp
#include <cuda_runtime.h>
#include <cuda_bf16.h>
#include <cuda.h>
#include <stdint.h>

#define GD192 1
#define GDOUT GD128
#define EVF 0
#define PFD 0
#define FIRSTW 1
#define MAPV 2
#define PREF 0
#define ONES 1
#define EARLYW 1
#define GD128 1

namespace {

constexpr int kS = 2048, kD = 1024, kDff = 3584;
constexpr int kThreads = 512;
constexpr int kCtas = 128;

constexpr uint32_t kSlot = 40960;
constexpr uint32_t kStageOff = 3 * kSlot;
constexpr uint32_t kKvOff = 4 * kSlot + 8192;
constexpr uint32_t kNKv = 5;
constexpr uint32_t kQOff = kKvOff + kNKv * 8192;
constexpr uint32_t kBarOff = kQOff + 2 * 8192;
constexpr uint32_t kOnesOff = kBarOff + 512;
constexpr uint32_t kSmemBytes = kOnesOff + 1024 + 1024;
constexpr uint32_t B_GFULL = 0, B_GEMPTY = 4, B_KVFULL = 8, B_KVEMPTY = 13, B_QFULL = 18, B_QEMPTY = 20, B_GST = 22,
                   B_AST = 24, B_STAT = 28, B_GST0 = 29, B_OUT = 30;

__device__ __align__(1024) uint8_t g_xn[16 * 16 * 16384];
__device__ __align__(1024) uint8_t g_q[32 * 2048 * 64];
__device__ __align__(1024) uint8_t g_kv[32 * 32 * 8192];
__device__ __align__(1024) uint8_t g_h[16 * 56 * 16384];
__device__ __align__(1024) uint8_t g_o[16 * 32 * 8192];
__device__ __align__(1024) float2 g_stat[2048];
constexpr int F_XN = 0, F_KV = 16, F_H = 48, F_O = 96, F_EPOCH = 160, F_COUNT = 161;
__device__ unsigned g_flags[F_COUNT * 32];

__device__ __forceinline__ uint32_t smem_u32(const void* p) { return (uint32_t)__cvta_generic_to_shared(p); }
__device__ __forceinline__ void wgmma_fence() { asm volatile("wgmma.fence.sync.aligned;\n" ::: "memory"); }
__device__ __forceinline__ void wgmma_commit() { asm volatile("wgmma.commit_group.sync.aligned;\n" ::: "memory"); }
template <int N>
__device__ __forceinline__ void wgmma_wait() { asm volatile("wgmma.wait_group.sync.aligned %0;\n" ::"n"(N) : "memory"); }
template <int N>
__device__ __forceinline__ void fence_regs(float (&r)[N]) {
#pragma unroll
  for (int i = 0; i < N; i++) asm volatile("" : "+f"(r[i])::"memory");
}
template <int N>
__device__ __forceinline__ void fence_regs(uint32_t (&r)[N]) {
#pragma unroll
  for (int i = 0; i < N; i++) asm volatile("" : "+r"(r[i])::"memory");
}
__device__ __forceinline__ uint64_t mk_desc(uint32_t lo, uint32_t hi) { return ((uint64_t)hi << 32) | lo; }
__host__ __device__ constexpr uint32_t desc_hi(uint32_t sbo, uint32_t swz) { return (sbo >> 4) | (swz << 30); }
__device__ __forceinline__ uint32_t desc_lo(uint32_t addr, uint32_t lbo) { return ((addr & 0x3FFFF) >> 4) | ((lbo >> 4) << 16); }

__device__ __forceinline__ void mbar_init(uint32_t bar, uint32_t cnt) {
  asm volatile("mbarrier.init.shared::cta.b64 [%0], %1;\n" ::"r"(bar), "r"(cnt) : "memory");
}
__device__ __forceinline__ void mbar_expect_tx(uint32_t bar, uint32_t bytes) {
  asm volatile("mbarrier.arrive.expect_tx.shared::cta.b64 _, [%0], %1;\n" ::"r"(bar), "r"(bytes) : "memory");
}
__device__ __forceinline__ void mbar_arrive(uint32_t bar) {
  asm volatile("mbarrier.arrive.shared::cta.b64 _, [%0];\n" ::"r"(bar) : "memory");
}
__device__ __forceinline__ void mbar_arrive_cta(uint32_t bar, uint32_t cta, uint32_t cnt) {
  asm volatile(
      "{\n.reg .b32 ra;\nmapa.shared::cluster.u32 ra, %0, %1;\nmbarrier.arrive.shared::cluster.b64 _, [ra], %2;\n}\n" ::"r"(bar),
      "r"(cta), "r"(cnt)
      : "memory");
}
__device__ __forceinline__ bool mbar_test(uint32_t bar, uint32_t parity) {
  uint32_t ok;
  asm volatile("{\n.reg .pred p;\nmbarrier.test_wait.parity.shared::cta.b64 p, [%1], %2;\nselp.u32 %0, 1, 0, p;\n}\n"
               : "=r"(ok)
               : "r"(bar), "r"(parity)
               : "memory");
  return ok;
}
__device__ __forceinline__ void mbar_wait(uint32_t bar, uint32_t parity) {
  asm volatile(
      "{\n.reg .pred p, q;\n.reg .u32 it;\nmov.u32 it, 0;\n"
      "LW_%=:\n"
      "mbarrier.try_wait.parity.shared::cta.b64 p, [%0], %1;\n"
      "@p bra LD_%=;\n"
      "add.u32 it, it, 1;\n"
      "setp.lt.u32 q, it, 0x400000;\n"
      "@q bra LW_%=;\n"
      "trap;\n"
      "LD_%=:\n}\n" ::"r"(bar), "r"(parity) : "memory");
}
__device__ __forceinline__ void mbar_wait_sleepy(uint32_t bar, uint32_t parity) {
  asm volatile(
      "{\n.reg .pred p, q;\n.reg .u32 it;\nmov.u32 it, 0;\n"
      "LW_%=:\n"
      "mbarrier.try_wait.parity.shared::cta.b64 p, [%0], %1, 20000;\n"
      "@p bra LD_%=;\n"
      "add.u32 it, it, 1;\n"
      "setp.lt.u32 q, it, 0x400000;\n"
      "@q bra LW_%=;\n"
      "trap;\n"
      "LD_%=:\n}\n" ::"r"(bar), "r"(parity) : "memory");
}
__device__ __forceinline__ uint32_t mapa(uint32_t addr, uint32_t cta) {
  uint32_t r;
  asm("mapa.shared::cluster.u32 %0, %1, %2;\n" : "=r"(r) : "r"(addr), "r"(cta));
  return r;
}
__device__ __forceinline__ void mbar_arrive_cluster_if(uint32_t addr, bool pred) {
  asm volatile("{\n.reg .pred p;\nsetp.ne.u32 p, %1, 0;\n@p mbarrier.arrive.shared::cluster.b64 _, [%0];\n}\n" ::"r"(addr),
               "r"((uint32_t)pred)
               : "memory");
}
__device__ __forceinline__ void flag_wait(const unsigned* f, unsigned target) {
  uint32_t it = 0;
#pragma unroll 1
  while (true) {
    unsigned v;
    asm volatile("ld.acquire.gpu.global.u32 %0, [%1];\n" : "=r"(v) : "l"(f) : "memory");
    if ((int)(v - target) >= 0) break;
    if (++it > (1u << 22)) asm volatile("trap;");
  }
  asm volatile("fence.proxy.async.global;\n" ::: "memory");
}
__device__ __forceinline__ void flag_add(unsigned* f, unsigned v) {
  asm volatile("red.relaxed.gpu.global.add.u32 [%0], %1;\n" ::"l"(f), "r"(v) : "memory");
}
__device__ __forceinline__ bool elect_one() {
  uint32_t p;
  asm volatile("{\n.reg .pred P;\nelect.sync _|P, 0xffffffff;\nselp.u32 %0, 1, 0, P;\n}\n" : "=r"(p));
  return p;
}
__device__ __forceinline__ void bulk_g2s(uint32_t dst, const void* src, uint32_t bytes, uint32_t bar) {
  asm volatile("cp.async.bulk.shared::cluster.global.mbarrier::complete_tx::bytes [%0], [%1], %2, [%3];\n" ::"r"(dst),
               "l"(src), "r"(bytes), "r"(bar)
               : "memory");
}
__device__ __forceinline__ void bulk_g2s_mc(uint32_t dst, const void* src, uint32_t bytes, uint32_t bar) {
  asm volatile(
      "cp.async.bulk.shared::cluster.global.mbarrier::complete_tx::bytes.multicast::cluster [%0], [%1], %2, [%3], %4;\n" ::"r"(dst),
      "l"(src), "r"(bytes), "r"(bar), "h"((uint16_t)3)
      : "memory");
}
__device__ __forceinline__ void bulk_s2g(void* dst, uint32_t src, uint32_t bytes) {
  asm volatile("cp.async.bulk.global.shared::cta.bulk_group [%0], [%1], %2;\n" ::"l"(dst), "r"(src), "r"(bytes) : "memory");
}
__device__ __forceinline__ void l2_prefetch(const void* src, uint32_t bytes) {
  asm volatile("cp.async.bulk.prefetch.L2.global [%0], %1;\n" ::"l"(src), "r"(bytes) : "memory");
}
__device__ __forceinline__ void bulk_commit() { asm volatile("cp.async.bulk.commit_group;\n" ::: "memory"); }
__device__ __forceinline__ void bulk_wait_read() { asm volatile("cp.async.bulk.wait_group.read 0;\n" ::: "memory"); }
__device__ __forceinline__ void bulk_wait_all() { asm volatile("cp.async.bulk.wait_group 0;\n" ::: "memory"); }
__device__ __forceinline__ void tma_2d(uint32_t dst, const CUtensorMap* m, int c0, int c1, uint32_t bar) {
  asm volatile(
      "cp.async.bulk.tensor.2d.shared::cluster.global.mbarrier::complete_tx::bytes [%0], [%1, {%3, %4}], [%2];\n" ::"r"(dst),
      "l"((uint64_t)m), "r"(bar), "r"(c0), "r"(c1)
      : "memory");
}
__device__ __forceinline__ uint64_t policy_evict_first() {
  uint64_t p;
  asm volatile("createpolicy.fractional.L2::evict_first.b64 %0, 1.0;\n" : "=l"(p));
  return p;
}
__device__ __forceinline__ void tma_3d_mc(uint32_t dst, const CUtensorMap* m, int c0, int c1, int c2, uint32_t bar, uint64_t pol) {
  asm volatile(
      "cp.async.bulk.tensor.3d.shared::cluster.global.mbarrier::complete_tx::bytes.multicast::cluster [%0], [%1, {%3, %4, %5}], "
      "[%2], %6;\n" ::"r"(dst),
      "l"((uint64_t)m), "r"(bar), "r"(c0), "r"(c1), "r"(c2), "h"((uint16_t)3)
      : "memory");
}
__device__ __forceinline__ void tma_4d_mc(uint32_t dst, const CUtensorMap* m, int c0, int c1, int c2, int c3, uint32_t bar, uint64_t pol) {
  asm volatile(
      "cp.async.bulk.tensor.4d.shared::cluster.global.mbarrier::complete_tx::bytes.multicast::cluster [%0], [%1, {%3, %4, %5, "
      "%6}], [%2], %7;\n" ::"r"(dst),
      "l"((uint64_t)m), "r"(bar), "r"(c0), "r"(c1), "r"(c2), "r"(c3), "h"((uint16_t)3)
      : "memory");
}
__device__ __forceinline__ void tma_pf_2d(const CUtensorMap* m, int c0, int c1) {
  asm volatile("cp.async.bulk.prefetch.tensor.2d.L2.global [%0, {%1, %2}];\n" ::"l"((uint64_t)m), "r"(c0), "r"(c1) : "memory");
}
__device__ __forceinline__ void tma_pf_3d(const CUtensorMap* m, int c0, int c1, int c2) {
  asm volatile("cp.async.bulk.prefetch.tensor.3d.L2.global [%0, {%1, %2, %3}];\n" ::"l"((uint64_t)m), "r"(c0), "r"(c1), "r"(c2) : "memory");
}
__device__ __forceinline__ void tma_pf_4d(const CUtensorMap* m, int c0, int c1, int c2, int c3) {
  asm volatile("cp.async.bulk.prefetch.tensor.4d.L2.global [%0, {%1, %2, %3, %4}];\n" ::"l"((uint64_t)m), "r"(c0), "r"(c1), "r"(c2),
               "r"(c3)
               : "memory");
}
__device__ __forceinline__ void tma_store_2d(const CUtensorMap* m, uint32_t src, int c0, int c1) {
  asm volatile("cp.async.bulk.tensor.2d.global.shared::cta.bulk_group [%0, {%2, %3}], [%1];\n" ::"l"((uint64_t)m), "r"(src),
               "r"(c0), "r"(c1)
               : "memory");
}
__device__ __forceinline__ void prefetch_map(const CUtensorMap* m) {
  asm volatile("prefetch.tensormap [%0];\n" ::"l"((uint64_t)m) : "memory");
}
__device__ __forceinline__ void fence_async_smem() { asm volatile("fence.proxy.async.shared::cta;\n" ::: "memory"); }
__device__ __forceinline__ void stsm4(uint32_t addr, uint32_t a, uint32_t b, uint32_t c, uint32_t d) {
  asm volatile("stmatrix.sync.aligned.m8n8.x4.shared.b16 [%0], {%1, %2, %3, %4};\n" ::"r"(addr), "r"(a), "r"(b), "r"(c), "r"(d)
               : "memory");
}
__device__ __forceinline__ void ldsm4(uint32_t addr, uint32_t& a, uint32_t& b, uint32_t& c, uint32_t& d) {
  asm volatile("ldmatrix.sync.aligned.m8n8.x4.shared.b16 {%0, %1, %2, %3}, [%4];\n"
               : "=r"(a), "=r"(b), "=r"(c), "=r"(d)
               : "r"(addr)
               : "memory");
}
__device__ __forceinline__ float ex2(float x) {
  float y;
  asm("ex2.approx.ftz.f32 %0, %1;" : "=f"(y) : "f"(x));
  return y;
}
__device__ __forceinline__ uint32_t pack_bf16(float lo, float hi) {
  uint32_t r;
  asm("cvt.rn.bf16x2.f32 %0, %1, %2;" : "=r"(r) : "f"(hi), "f"(lo));
  return r;
}
__device__ __forceinline__ uint32_t pack_bf16_relu(float lo, float hi) {
  uint32_t r;
  asm("cvt.rn.relu.bf16x2.f32 %0, %1, %2;" : "=r"(r) : "f"(hi), "f"(lo));
  return r;
}
__device__ __forceinline__ float bf_lo(uint32_t v) {
  uint32_t r;
  asm("prmt.b32 %0, %1, 0, 0x1044;" : "=r"(r) : "r"(v));
  return __uint_as_float(r);
}
__device__ __forceinline__ float bf_hi(uint32_t v) { return __uint_as_float(v & 0xffff0000u); }
__device__ __forceinline__ float bf_round(float x) { return __bfloat162float(__float2bfloat16_rn(x)); }
__device__ __forceinline__ void named_sync(int id) { asm volatile("bar.sync %0, 128;\n" ::"r"(id) : "memory"); }
__device__ __forceinline__ void cluster_arrive() { asm volatile("barrier.cluster.arrive.relaxed.aligned;\n" ::: "memory"); }
__device__ __forceinline__ void cluster_wait() { asm volatile("barrier.cluster.wait.acquire.aligned;\n" ::: "memory"); }
#define TM(cond, idx)
#define TACC(acc, stmt) do { stmt; } while (0)
#define TPUT(cond, idx, v)

template <int TB>
__device__ __forceinline__ void wgmma_ss_n192(float (&d)[96], uint64_t da, uint64_t db, int scale_d) {
  asm volatile(
      "{\n.reg .pred p;\nsetp.ne.b32 p, %98, 0;\n"
      "wgmma.mma_async.sync.aligned.m64n192k16.f32.bf16.bf16 {"
      "%0, %1, %2, %3, %4, %5, %6, %7, %8, %9, %10, %11, %12, %13, %14, %15, "
      "%16, %17, %18, %19, %20, %21, %22, %23, %24, %25, %26, %27, %28, %29, %30, %31, "
      "%32, %33, %34, %35, %36, %37, %38, %39, %40, %41, %42, %43, %44, %45, %46, %47, "
      "%48, %49, %50, %51, %52, %53, %54, %55, %56, %57, %58, %59, %60, %61, %62, %63, "
      "%64, %65, %66, %67, %68, %69, %70, %71, %72, %73, %74, %75, %76, %77, %78, %79, "
      "%80, %81, %82, %83, %84, %85, %86, %87, %88, %89, %90, %91, %92, %93, %94, %95}, %96, %97, p, 1, 1, 0, %99;\n}\n"
      : "+f"(d[0]), "+f"(d[1]), "+f"(d[2]), "+f"(d[3]), "+f"(d[4]), "+f"(d[5]), "+f"(d[6]), "+f"(d[7]),
        "+f"(d[8]), "+f"(d[9]), "+f"(d[10]), "+f"(d[11]), "+f"(d[12]), "+f"(d[13]), "+f"(d[14]), "+f"(d[15]),
        "+f"(d[16]), "+f"(d[17]), "+f"(d[18]), "+f"(d[19]), "+f"(d[20]), "+f"(d[21]), "+f"(d[22]), "+f"(d[23]),
        "+f"(d[24]), "+f"(d[25]), "+f"(d[26]), "+f"(d[27]), "+f"(d[28]), "+f"(d[29]), "+f"(d[30]), "+f"(d[31]),
        "+f"(d[32]), "+f"(d[33]), "+f"(d[34]), "+f"(d[35]), "+f"(d[36]), "+f"(d[37]), "+f"(d[38]), "+f"(d[39]),
        "+f"(d[40]), "+f"(d[41]), "+f"(d[42]), "+f"(d[43]), "+f"(d[44]), "+f"(d[45]), "+f"(d[46]), "+f"(d[47]),
        "+f"(d[48]), "+f"(d[49]), "+f"(d[50]), "+f"(d[51]), "+f"(d[52]), "+f"(d[53]), "+f"(d[54]), "+f"(d[55]),
        "+f"(d[56]), "+f"(d[57]), "+f"(d[58]), "+f"(d[59]), "+f"(d[60]), "+f"(d[61]), "+f"(d[62]), "+f"(d[63]),
        "+f"(d[64]), "+f"(d[65]), "+f"(d[66]), "+f"(d[67]), "+f"(d[68]), "+f"(d[69]), "+f"(d[70]), "+f"(d[71]),
        "+f"(d[72]), "+f"(d[73]), "+f"(d[74]), "+f"(d[75]), "+f"(d[76]), "+f"(d[77]), "+f"(d[78]), "+f"(d[79]),
        "+f"(d[80]), "+f"(d[81]), "+f"(d[82]), "+f"(d[83]), "+f"(d[84]), "+f"(d[85]), "+f"(d[86]), "+f"(d[87]),
        "+f"(d[88]), "+f"(d[89]), "+f"(d[90]), "+f"(d[91]), "+f"(d[92]), "+f"(d[93]), "+f"(d[94]), "+f"(d[95])
      : "l"(da), "l"(db), "r"(scale_d), "n"(TB));
}
template <int TB>
__device__ __forceinline__ void wgmma_ss_n128(float (&d)[96], uint64_t da, uint64_t db, int scale_d) {
  asm volatile(
      "{\n.reg .pred p;\nsetp.ne.b32 p, %66, 0;\n"
      "wgmma.mma_async.sync.aligned.m64n128k16.f32.bf16.bf16 {"
      "%0, %1, %2, %3, %4, %5, %6, %7, %8, %9, %10, %11, %12, %13, %14, %15, "
      "%16, %17, %18, %19, %20, %21, %22, %23, %24, %25, %26, %27, %28, %29, %30, %31, "
      "%32, %33, %34, %35, %36, %37, %38, %39, %40, %41, %42, %43, %44, %45, %46, %47, "
      "%48, %49, %50, %51, %52, %53, %54, %55, %56, %57, %58, %59, %60, %61, %62, %63}, %64, %65, p, 1, 1, 0, %67;\n}\n"
      : "+f"(d[0]), "+f"(d[1]), "+f"(d[2]), "+f"(d[3]), "+f"(d[4]), "+f"(d[5]), "+f"(d[6]), "+f"(d[7]),
        "+f"(d[8]), "+f"(d[9]), "+f"(d[10]), "+f"(d[11]), "+f"(d[12]), "+f"(d[13]), "+f"(d[14]), "+f"(d[15]),
        "+f"(d[16]), "+f"(d[17]), "+f"(d[18]), "+f"(d[19]), "+f"(d[20]), "+f"(d[21]), "+f"(d[22]), "+f"(d[23]),
        "+f"(d[24]), "+f"(d[25]), "+f"(d[26]), "+f"(d[27]), "+f"(d[28]), "+f"(d[29]), "+f"(d[30]), "+f"(d[31]),
        "+f"(d[32]), "+f"(d[33]), "+f"(d[34]), "+f"(d[35]), "+f"(d[36]), "+f"(d[37]), "+f"(d[38]), "+f"(d[39]),
        "+f"(d[40]), "+f"(d[41]), "+f"(d[42]), "+f"(d[43]), "+f"(d[44]), "+f"(d[45]), "+f"(d[46]), "+f"(d[47]),
        "+f"(d[48]), "+f"(d[49]), "+f"(d[50]), "+f"(d[51]), "+f"(d[52]), "+f"(d[53]), "+f"(d[54]), "+f"(d[55]),
        "+f"(d[56]), "+f"(d[57]), "+f"(d[58]), "+f"(d[59]), "+f"(d[60]), "+f"(d[61]), "+f"(d[62]), "+f"(d[63])
      : "l"(da), "l"(db), "r"(scale_d), "n"(TB));
}
template <int TB>
__device__ __forceinline__ void wgmma_ss_n64(float (&d)[32], uint64_t da, uint64_t db, int scale_d) {
  asm volatile(
      "{\n.reg .pred p;\nsetp.ne.b32 p, %34, 0;\n"
      "wgmma.mma_async.sync.aligned.m64n64k16.f32.bf16.bf16 {"
      "%0, %1, %2, %3, %4, %5, %6, %7, %8, %9, %10, %11, %12, %13, %14, %15, "
      "%16, %17, %18, %19, %20, %21, %22, %23, %24, %25, %26, %27, %28, %29, %30, %31}, %32, %33, p, 1, 1, 0, %35;\n}\n"
      : "+f"(d[0]), "+f"(d[1]), "+f"(d[2]), "+f"(d[3]), "+f"(d[4]), "+f"(d[5]), "+f"(d[6]), "+f"(d[7]),
        "+f"(d[8]), "+f"(d[9]), "+f"(d[10]), "+f"(d[11]), "+f"(d[12]), "+f"(d[13]), "+f"(d[14]), "+f"(d[15]),
        "+f"(d[16]), "+f"(d[17]), "+f"(d[18]), "+f"(d[19]), "+f"(d[20]), "+f"(d[21]), "+f"(d[22]), "+f"(d[23]),
        "+f"(d[24]), "+f"(d[25]), "+f"(d[26]), "+f"(d[27]), "+f"(d[28]), "+f"(d[29]), "+f"(d[30]), "+f"(d[31])
      : "l"(da), "l"(db), "r"(scale_d), "n"(TB));
}
template <int TB>
__device__ __forceinline__ void wgmma_rs_n32(float (&d)[16], uint32_t a0, uint32_t a1, uint32_t a2, uint32_t a3,
                                             uint64_t db, int scale_d) {
  asm volatile(
      "{\n.reg .pred p;\nsetp.ne.b32 p, %21, 0;\n"
      "wgmma.mma_async.sync.aligned.m64n32k16.f32.bf16.bf16 {"
      "%0, %1, %2, %3, %4, %5, %6, %7, %8, %9, %10, %11, %12, %13, %14, %15}, {%16, %17, %18, %19}, %20, p, 1, 1, %22;\n}\n"
      : "+f"(d[0]), "+f"(d[1]), "+f"(d[2]), "+f"(d[3]), "+f"(d[4]), "+f"(d[5]), "+f"(d[6]), "+f"(d[7]),
        "+f"(d[8]), "+f"(d[9]), "+f"(d[10]), "+f"(d[11]), "+f"(d[12]), "+f"(d[13]), "+f"(d[14]), "+f"(d[15])
      : "r"(a0), "r"(a1), "r"(a2), "r"(a3), "l"(db), "r"(scale_d), "n"(TB));
}
template <int TB>
__device__ __forceinline__ void wgmma_rs_n40(float (&d)[20], uint32_t a0, uint32_t a1, uint32_t a2, uint32_t a3,
                                             uint64_t db, int scale_d) {
  asm volatile(
      "{\n.reg .pred p;\nsetp.ne.b32 p, %25, 0;\n"
      "wgmma.mma_async.sync.aligned.m64n40k16.f32.bf16.bf16 {"
      "%0, %1, %2, %3, %4, %5, %6, %7, %8, %9, %10, %11, %12, %13, %14, %15, "
      "%16, %17, %18, %19}, {%20, %21, %22, %23}, %24, p, 1, 1, %26;\n}\n"
      : "+f"(d[0]), "+f"(d[1]), "+f"(d[2]), "+f"(d[3]), "+f"(d[4]), "+f"(d[5]), "+f"(d[6]), "+f"(d[7]),
        "+f"(d[8]), "+f"(d[9]), "+f"(d[10]), "+f"(d[11]), "+f"(d[12]), "+f"(d[13]), "+f"(d[14]), "+f"(d[15]),
        "+f"(d[16]), "+f"(d[17]), "+f"(d[18]), "+f"(d[19])
      : "r"(a0), "r"(a1), "r"(a2), "r"(a3), "l"(db), "r"(scale_d), "n"(TB));
}

template <int N>
__device__ __forceinline__ void wgmma_gemm(float (&d)[96], uint64_t da, uint64_t db, int sc) {
  if constexpr (N == 192) wgmma_ss_n192<1>(d, da, db, sc);
  else wgmma_ss_n128<1>(d, da, db, sc);
}

__device__ __forceinline__ uint32_t next_slot(int pos, bool first_tile, uint32_t& r3) {
  const bool x = (pos & 3) == 2 && (first_tile || pos >= 6);
  const uint32_t s = x ? 3u : r3;
  r3 = x ? r3 : ((r3 == 2) ? 0u : r3 + 1);
  return s;
}
__device__ __forceinline__ bool out_kb_is_attn(int kb) { return (kb >= 40 && kb < 48) || kb >= 64; }

#define GWAIT(bar, par) do { if (!ready) mbar_wait(bar, par); } while (0)
struct GemmState {
  uint32_t lo0, bars, rel_addr;
  uint32_t phases, r3, s;
  bool rel_lane;
  uint32_t twait;
};
struct BFmt { uint32_t lbo, hi, k1, k2; };

template <int N>
__device__ __forceinline__ void mma_half(float (&d)[96], uint32_t a_lo, uint32_t a_hi, uint32_t a_k2, uint32_t b_lo, const BFmt b,
                                         int k, int sc) {
  wgmma_gemm<N>(d, mk_desc(a_lo + (k >> 1) * a_k2 + (k & 1) * 2, a_hi), mk_desc(b_lo + (k >> 1) * b.k2 + (k & 1) * b.k1, b.hi), sc);
}
template <int N>
__device__ __forceinline__ void tile_head(float (&d0)[96], GemmState& g, const BFmt b) {
  g.s = next_slot(0, false, g.r3);
  const bool ready = false;
  uint32_t& twait = g.twait;
  (void)twait;
  GWAIT(g.bars + (B_GFULL + g.s) * 8, (g.phases >> g.s) & 1);
  const uint32_t a_lo = g.lo0 + (1u << 16) + g.s * (kSlot >> 4), b_lo = g.lo0 + (16384 >> 4) + ((b.lbo >> 4) << 16) + g.s * (kSlot >> 4);
  fence_regs(d0);
  wgmma_fence();
#pragma unroll
  for (int k = 0; k < 4; k++) mma_half<N>(d0, a_lo, desc_hi(1024, 1), 64 >> 4, b_lo, b, k, k > 0);
  wgmma_commit();
}
template <int N, int NKB, int GD, bool OUTK>
__device__ __forceinline__ void tile_body(float (&d0)[96], float (&d1)[96], GemmState& g, const BFmt b) {
  const uint32_t a_c = g.lo0 + (1u << 16), b_c = g.lo0 + (16384 >> 4) + ((b.lbo >> 4) << 16);
  uint32_t s = g.s, rel, a_lo, b_lo;
  uint32_t a_hi = desc_hi(1024, 1), a_half = 8192 >> 4, a_k2 = 64 >> 4;
  uint32_t& twait = g.twait;
  (void)twait;
  bool ready;
  auto prepare = [&](int kb) {
    g.phases ^= 1u << s;
    rel = g.rel_addr + s * 8;
    s = next_slot(kb, false, g.r3);
    a_lo = a_c + s * (kSlot >> 4);
    b_lo = b_c + s * (kSlot >> 4);
    if (OUTK) {
      const bool at = out_kb_is_attn(kb);
      a_hi = at ? desc_hi(512, 2) : desc_hi(1024, 1);
      a_half = at ? 4096 >> 4 : 8192 >> 4;
      a_k2 = at ? 8192 >> 4 : 64 >> 4;
    }
    ready = mbar_test(g.bars + (B_GFULL + s) * 8, (g.phases >> s) & 1);
  };
  {
    const uint32_t ca = a_c + s * (kSlot >> 4) + (8192 >> 4), cb = b_c + s * (kSlot >> 4);
    fence_regs(d1);
    wgmma_fence();
#pragma unroll
    for (int k = 0; k < 4; k++) {
      wgmma_wait<GD>();
      mma_half<N>(d1, ca, desc_hi(1024, 1), 64 >> 4, cb, b, k, k > 0);
      wgmma_commit();
      if (k == 1) prepare(1);
    }
  }
#pragma unroll 1
  for (int kb = 1; kb < NKB - 1; kb++) {
    GWAIT(g.bars + (B_GFULL + s) * 8, (g.phases >> s) & 1);
    const uint32_t ca_lo = a_lo, cb_lo = b_lo, ca_hi = a_hi, ca_half = a_half, ca_k2 = a_k2, crel = rel;
    wgmma_fence();
#pragma unroll
    for (int k = 0; k < 4; k++) {
      wgmma_wait<GD>();
      mma_half<N>(d0, ca_lo, ca_hi, ca_k2, cb_lo, b, k, 1);
      wgmma_commit();
      if (2 * k == GD) mbar_arrive_cluster_if(crel, g.rel_lane);
      wgmma_wait<GD>();
      mma_half<N>(d1, ca_lo + ca_half, ca_hi, ca_k2, cb_lo, b, k, 1);
      wgmma_commit();
      if (2 * k + 1 == GD) mbar_arrive_cluster_if(crel, g.rel_lane);
      if (k == 2) prepare(kb + 1);
    }
  }
  GWAIT(g.bars + (B_GFULL + s) * 8, (g.phases >> s) & 1);
  g.phases ^= 1u << s;
  g.s = s;
  wgmma_fence();
#pragma unroll
  for (int k = 0; k < 4; k++) {
    wgmma_wait<GD>();
    mma_half<N>(d0, a_lo, a_hi, a_k2, b_lo, b, k, 1);
    wgmma_commit();
  }
#pragma unroll
  for (int k = 0; k < 4; k++) mma_half<N>(d1, a_lo + a_half, a_hi, a_k2, b_lo, b, k, 1);
  wgmma_commit();
  wgmma_wait<1>();
  fence_regs(d0);
}
__device__ __forceinline__ void tile_drain(float (&d1)[96], GemmState& g) {
  wgmma_wait<0>();
  fence_regs(d1);
  mbar_arrive_cluster_if(g.rel_addr + g.s * 8, g.rel_lane);
}

__device__ __forceinline__ void tile_first(float (&d0)[96], float (&d1)[96], float (&cs)[6], uint32_t sb, uint32_t rank,
                                           GemmState& g, const BFmt b) {
  const int lane = threadIdx.x & 31, w = (threadIdx.x >> 5) & 3;
  const uint32_t a_c = g.lo0 + (1u << 16), b_c = g.lo0 + (16384 >> 4) + ((b.lbo >> 4) << 16);
  uint32_t& twait = g.twait;
  (void)twait;
  bool ready = false;
  uint32_t prev = 0;
  const uint32_t cs_base = sb + 16384 + rank * 12288 + lane * 64 + ((w ^ ((lane >> 1) & 3)) << 4);
#pragma unroll 1
  for (int kb = 0; kb < 16; kb++) {
    const uint32_t s = (kb & 3) ^ ((kb >> 1) & 1);
    GWAIT(g.bars + (B_GFULL + s) * 8, (kb >> 2) & 1);
    const uint32_t a_lo = a_c + s * (kSlot >> 4), b_lo = b_c + s * (kSlot >> 4);
    wgmma_fence();
#pragma unroll
    for (int k = 0; k < 4; k++) mma_half<192>(d0, a_lo, desc_hi(1024, 1), 64 >> 4, b_lo, b, k, (k > 0) ? 1 : (kb > 0));
    wgmma_commit();
#pragma unroll
    for (int k = 0; k < 4; k++) mma_half<192>(d1, a_lo + (8192 >> 4), desc_hi(1024, 1), 64 >> 4, b_lo, b, k, (k > 0) ? 1 : (kb > 0));
    wgmma_commit();
    wgmma_wait<2>();
    mbar_arrive_cluster_if(g.rel_addr + prev * 8, g.rel_lane && kb > 0 && kb < 15);
    prev = s;
#pragma unroll
    for (int h = 0; h < 2; h++) {
      uint32_t bq[3][4];
#pragma unroll
      for (int i = 0; i < 3; i++)
        asm volatile("ldmatrix.sync.aligned.m8n8.x4.trans.shared.b16 {%0, %1, %2, %3}, [%4];\n"
                     : "=r"(bq[i][0]), "=r"(bq[i][1]), "=r"(bq[i][2]), "=r"(bq[i][3])
                     : "r"(cs_base + s * kSlot + (3 * h + i) * 2048)
                     : "memory");
#pragma unroll
      for (int i = 0; i < 3; i++)
        cs[3 * h + i] += ((bf_lo(bq[i][0]) + bf_hi(bq[i][0])) + (bf_lo(bq[i][1]) + bf_hi(bq[i][1]))) +
                         ((bf_lo(bq[i][2]) + bf_hi(bq[i][2])) + (bf_lo(bq[i][3]) + bf_hi(bq[i][3])));
    }
    asm volatile("" : "+f"(cs[0]), "+f"(cs[1]), "+f"(cs[2]), "+f"(cs[3]), "+f"(cs[4]), "+f"(cs[5])::"memory");
    ready = mbar_test(g.bars + (B_GFULL + (((kb + 1) & 3) ^ (((kb + 1) >> 1) & 1))) * 8, ((kb + 1) >> 2) & 1);
  }
  wgmma_wait<1>();
  fence_regs(d0);
  g.s = 2;
}

__device__ __forceinline__ void epi_publish(uint32_t bar, int lane) {
  fence_async_smem();
  __syncwarp();
  if (lane == 0) mbar_arrive(bar);
}
constexpr float kQScale = 0.17677669529663687f * 1.4426950408889634f;
template <int NJ, int NQ>
__device__ __forceinline__ void epi_qkv(const float (&d)[96], uint32_t base, uint32_t sw, uint32_t scol) {
#pragma unroll
  for (int jj = 0; jj < NJ; jj++) {
    const float f = jj < NQ ? kQScale : 1.f;
    stsm4(base + (jj >> 1) * 8192 + ((((jj & 1) * 2 + scol) ^ sw) << 4), pack_bf16(d[8 * jj] * f, d[8 * jj + 1] * f),
          pack_bf16(d[8 * jj + 2] * f, d[8 * jj + 3] * f), pack_bf16(d[8 * jj + 4] * f, d[8 * jj + 5] * f),
          pack_bf16(d[8 * jj + 6] * f, d[8 * jj + 7] * f));
  }
}
template <int R>
__device__ __forceinline__ void epi_qkv_ln(const float (&d)[96], uint32_t cs_addr, float2 s0, float2 s1, uint32_t base,
                                           uint32_t sw, uint32_t scol) {
  float c[4], cn[4];
  asm volatile("ld.shared.v2.f32 {%0, %1}, [%2];\n" : "=f"(cn[0]), "=f"(cn[1]) : "r"(cs_addr + R * 128));
  asm volatile("ld.shared.v2.f32 {%0, %1}, [%2];\n" : "=f"(cn[2]), "=f"(cn[3]) : "r"(cs_addr + R * 128 + 32));
#pragma unroll
  for (int q = 0; q < 6; q++) {
    const int jj = (q >> 1) * 4 + 2 * R + (q & 1), jn = ((q + 1) >> 1) * 4 + 2 * R + ((q + 1) & 1);
    const float f0 = jj < 4 ? kQScale * s0.y : s0.y, f1 = jj < 4 ? kQScale * s1.y : s1.y;
#pragma unroll
    for (int i = 0; i < 4; i++) c[i] = cn[i];
    if (q < 5) {
      asm volatile("ld.shared.v2.f32 {%0, %1}, [%2];\n" : "=f"(cn[0]), "=f"(cn[1]) : "r"(cs_addr + jn * 64));
      asm volatile("ld.shared.v2.f32 {%0, %1}, [%2];\n" : "=f"(cn[2]), "=f"(cn[3]) : "r"(cs_addr + jn * 64 + 32));
    }
    float v[8];
#pragma unroll
    for (int i = 0; i < 8; i++) {
      const float ci = c[(i >> 2) * 2 + (i & 1)];
      v[i] = (i & 2) ? fmaf(-s1.x, ci, d[8 * jj + i]) * f1 : fmaf(-s0.x, ci, d[8 * jj + i]) * f0;
    }
    stsm4(base + (jj >> 1) * 8192 + ((((jj & 1) * 2 + scol) ^ sw) << 4), pack_bf16(v[0], v[1]), pack_bf16(v[2], v[3]),
          pack_bf16(v[4], v[5]), pack_bf16(v[6], v[7]));
  }
}
template <int J0, int J1>
__device__ __forceinline__ void epi_relu(const float (&d)[96], uint32_t base, uint32_t sw, uint32_t scol) {
#pragma unroll
  for (int jj = J0; jj < J1; jj++)
    stsm4(base + ((jj - J0) >> 2) * 16384 + (((((jj - J0) & 3) * 2 + scol) ^ sw) << 4), pack_bf16_relu(d[8 * jj], d[8 * jj + 1]),
          pack_bf16_relu(d[8 * jj + 2], d[8 * jj + 3]), pack_bf16_relu(d[8 * jj + 4], d[8 * jj + 5]),
          pack_bf16_relu(d[8 * jj + 6], d[8 * jj + 7]));
}
template <int CH>
__device__ __forceinline__ void epi_out(const float (&d)[96], uint32_t base, uint32_t sw, uint32_t scol) {
  uint32_t x[4][4];
#pragma unroll
  for (int q = 0; q < 4; q++) ldsm4(base + CH * 16384 + (((q * 2 + scol) ^ sw) << 4), x[q][0], x[q][1], x[q][2], x[q][3]);
#pragma unroll
  for (int q = 0; q < 4; q++) {
    const int jj = 4 * CH + q;
    stsm4(base + CH * 16384 + (((q * 2 + scol) ^ sw) << 4), pack_bf16(d[8 * jj] + bf_lo(x[q][0]), d[8 * jj + 1] + bf_hi(x[q][0])),
          pack_bf16(d[8 * jj + 2] + bf_lo(x[q][1]), d[8 * jj + 3] + bf_hi(x[q][1])),
          pack_bf16(d[8 * jj + 4] + bf_lo(x[q][2]), d[8 * jj + 5] + bf_hi(x[q][2])),
          pack_bf16(d[8 * jj + 6] + bf_lo(x[q][3]), d[8 * jj + 7] + bf_hi(x[q][3])));
  }
}

__device__ __noinline__ void attn_exact(float* o_out, uint32_t q_smem_row_addr, const uint8_t* kv_head) {
  const int lane = threadIdx.x & 31, g = lane >> 2, t = lane & 3;
  uint32_t qa[2][4];
  {
    const int r = (lane & 7) + ((lane >> 3) & 1) * 8;
#pragma unroll
    for (int k = 0; k < 2; k++) {
      const int c16 = 2 * k + (lane >> 4);
      ldsm4(q_smem_row_addr + r * 64 + ((c16 ^ ((r >> 1) & 3)) << 4), qa[k][0], qa[k][1], qa[k][2], qa[k][3]);
    }
  }
  float o[16];
#pragma unroll
  for (int i = 0; i < 16; i++) o[i] = 0.f;
  float m0 = -INFINITY, m1 = -INFINITY, l0 = 0.f, l1 = 0.f;
#pragma unroll 1
  for (int kc = 0; kc < kS / 16; kc++) {
    const uint8_t* kt = kv_head + (kc >> 2) * 8192;
    const int k0 = (kc & 3) * 16;
    float s[2][4];
#pragma unroll
    for (int nb = 0; nb < 2; nb++) {
      s[nb][0] = s[nb][1] = s[nb][2] = s[nb][3] = 0.f;
      const int key = k0 + nb * 8 + g;
#pragma unroll
      for (int k = 0; k < 2; k++) {
        const uint32_t b0 = __ldcg((const uint32_t*)(kt + key * 64 + (((2 * k) ^ ((key >> 1) & 3)) << 4) + t * 4));
        const uint32_t b1 = __ldcg((const uint32_t*)(kt + key * 64 + (((2 * k + 1) ^ ((key >> 1) & 3)) << 4) + t * 4));
        asm volatile(
            "mma.sync.aligned.m16n8k16.row.col.f32.bf16.bf16.f32 {%0,%1,%2,%3}, {%4,%5,%6,%7}, {%8,%9}, {%0,%1,%2,%3};\n"
            : "+f"(s[nb][0]), "+f"(s[nb][1]), "+f"(s[nb][2]), "+f"(s[nb][3])
            : "r"(qa[k][0]), "r"(qa[k][1]), "r"(qa[k][2]), "r"(qa[k][3]), "r"(b0), "r"(b1));
      }
    }
    float x0 = fmaxf(fmaxf(s[0][0], s[0][1]), fmaxf(s[1][0], s[1][1]));
    float x1 = fmaxf(fmaxf(s[0][2], s[0][3]), fmaxf(s[1][2], s[1][3]));
    x0 = fmaxf(x0, __shfl_xor_sync(~0u, x0, 1)); x1 = fmaxf(x1, __shfl_xor_sync(~0u, x1, 1));
    x0 = fmaxf(x0, __shfl_xor_sync(~0u, x0, 2)); x1 = fmaxf(x1, __shfl_xor_sync(~0u, x1, 2));
    x0 = fmaxf(x0, m0); x1 = fmaxf(x1, m1);
    const float c0 = ex2(m0 - x0), c1 = ex2(m1 - x1);
    m0 = x0; m1 = x1;
    uint32_t p[4];
    {
      const float e00 = ex2(s[0][0] - m0), e01 = ex2(s[0][1] - m0), e02 = ex2(s[0][2] - m1), e03 = ex2(s[0][3] - m1);
      const float e10 = ex2(s[1][0] - m0), e11 = ex2(s[1][1] - m0), e12 = ex2(s[1][2] - m1), e13 = ex2(s[1][3] - m1);
      l0 = l0 * c0 + (e00 + e01 + e10 + e11);
      l1 = l1 * c1 + (e02 + e03 + e12 + e13);
      p[0] = pack_bf16(e00, e01); p[1] = pack_bf16(e02, e03); p[2] = pack_bf16(e10, e11); p[3] = pack_bf16(e12, e13);
    }
    const uint8_t* vt = kt + 4096;
#pragma unroll
    for (int nb = 0; nb < 4; nb++) {
      uint32_t hv[4];
#pragma unroll
      for (int i = 0; i < 4; i++) {
        const int key = k0 + 2 * t + (i & 1) + (i >> 1) * 8;
        hv[i] = __ldcg((const unsigned short*)(vt + key * 64 + ((nb ^ ((key >> 1) & 3)) << 4) + g * 2));
      }
      const uint32_t b0 = hv[0] | (hv[1] << 16), b1 = hv[2] | (hv[3] << 16);
      o[4 * nb] *= c0; o[4 * nb + 1] *= c0; o[4 * nb + 2] *= c1; o[4 * nb + 3] *= c1;
      asm volatile(
          "mma.sync.aligned.m16n8k16.row.col.f32.bf16.bf16.f32 {%0,%1,%2,%3}, {%4,%5,%6,%7}, {%8,%9}, {%0,%1,%2,%3};\n"
          : "+f"(o[4 * nb]), "+f"(o[4 * nb + 1]), "+f"(o[4 * nb + 2]), "+f"(o[4 * nb + 3])
          : "r"(p[0]), "r"(p[1]), "r"(p[2]), "r"(p[3]), "r"(b0), "r"(b1));
    }
  }
  l0 += __shfl_xor_sync(~0u, l0, 1); l1 += __shfl_xor_sync(~0u, l1, 1);
  l0 += __shfl_xor_sync(~0u, l0, 2); l1 += __shfl_xor_sync(~0u, l1, 2);
  const float i0 = 1.f / l0, i1 = 1.f / l1;
#pragma unroll
  for (int nb = 0; nb < 4; nb++) {
    o_out[4 * nb] = o[4 * nb] * i0; o_out[4 * nb + 1] = o[4 * nb + 1] * i0;
    o_out[4 * nb + 2] = o[4 * nb + 2] * i1; o_out[4 * nb + 3] = o[4 * nb + 3] * i1;
  }
}

struct Params {
  CUtensorMap wqkv, w1a, w1b, w2, wo, x, out;
  const __nv_bfloat16* xptr;
  const uint8_t *wqkv_p, *w1_p, *w2_p, *wo_p;
};

__global__ void __cluster_dims__(2, 1, 1) __launch_bounds__(kThreads, 1) fused_block_kernel(const __grid_constant__ Params P) {
  extern __shared__ __align__(1024) uint8_t smem_raw[];
  const uint32_t sb = (smem_u32(smem_raw) + 1023) & ~1023u;
  const uint32_t bars = sb + kBarOff;
  const int warp = __shfl_sync(~0u, threadIdx.x >> 5, 0);
  const int lane = threadIdx.x & 31;
  const uint32_t rank = blockIdx.x & 1;
  const int cl = blockIdx.x >> 1;
  const int c = ((cl & 1) << 2) | ((cl >> 3) & 3);
  const int m = (((cl & 6) | (cl >> 5)) << 1) + rank;
  TM(threadIdx.x == 0, 0);
  TPUT(threadIdx.x == 0, 60, clk32());

  if (threadIdx.x == 0) {
    for (int i = 0; i < 4; i++) { mbar_init(bars + (B_GFULL + i) * 8, 1); mbar_init(bars + (B_GEMPTY + i) * 8, 8); }
    for (int i = 0; i < (int)kNKv; i++) { mbar_init(bars + (B_KVFULL + i) * 8, 1); mbar_init(bars + (B_KVEMPTY + i) * 8, 16); }
    for (int i = 0; i < 2; i++) { mbar_init(bars + (B_QFULL + i) * 8, 1); mbar_init(bars + (B_QEMPTY + i) * 8, 1); mbar_init(bars + (B_GST + i) * 8, 4); }
    for (int i = 0; i < 4; i++) mbar_init(bars + (B_AST + i) * 8, 4);
    mbar_init(bars + B_STAT * 8, 1);
    mbar_init(bars + B_GST0 * 8, 4);
    for (int i = 0; i < 4; i++) mbar_init(bars + (B_OUT + i) * 8, 4);
    asm volatile("fence.mbarrier_init.release.cluster;\n" ::: "memory");
  }
  if (threadIdx.x == 32) {
    unsigned e;
    asm volatile("ld.relaxed.gpu.global.u32 %0, [%1];\n" : "=r"(e) : "l"(&g_flags[F_EPOCH * 32]) : "memory");
    asm volatile("st.shared.u32 [%0], %1;\n" ::"r"(bars + 480), "r"(e + 1) : "memory");
  }
  if (ONES && threadIdx.x >= 256) {
    asm volatile("st.shared.b32 [%0], %1;\n" ::"r"(sb + kOnesOff + (threadIdx.x - 256) * 4), "r"(0x3f803f80u) : "memory");
    fence_async_smem();
  }
  __syncthreads();
  cluster_arrive();

  if (warp < 4) {
    asm volatile("setmaxnreg.dec.sync.aligned.u32 32;\n");
    if (warp == 1 && lane == 0) { prefetch_map(&P.wqkv); prefetch_map(&P.w1a); prefetch_map(&P.w1b); prefetch_map(&P.w2); prefetch_map(&P.wo); }
    if (warp == 0 && lane == 0) {
      for (int kb = 0; kb < 4; kb++) {
        const int s = kb ^ (kb >> 1);
        mbar_expect_tx(bars + (B_GFULL + s) * 8, 16384 + 24576);
        tma_2d(sb + s * kSlot, &P.x, kb * 64, 128 * m, bars + (B_GFULL + s) * 8);
      }
    }
    if (warp == 2 && lane == 0) prefetch_map(&P.out);
    __syncwarp();
    cluster_wait();
    unsigned ep;
    asm volatile("ld.shared.u32 %0, [%1];\n" : "=r"(ep) : "r"(bars + 480) : "memory");
    ep = __shfl_sync(~0u, ep, 0);
    const bool lead = elect_one();
    {
      if (warp == 0) {
        uint32_t ph = 0xf, r3 = 0;
        const uint64_t pol = policy_evict_first();
        uint32_t full, dst;
        auto acquire = [&](int pos, bool first, uint32_t bytes) {
          const uint32_t s = next_slot(pos, first, r3);
          full = bars + s * 8;
          dst = sb + s * kSlot;
          const uint32_t par = (ph >> s) & 1;
          ph ^= 1u << s;
          mbar_wait_sleepy(full + B_GEMPTY * 8, par);
          if (bytes) if (lead) mbar_expect_tx(full, bytes);
        };
        const int kr = rank * 32;
        auto pfk = [&](int kb) { return ((kb & 8) + (m >> 1)) * 64 + kr; };
#pragma unroll 1
        for (int kb = 0; kb < 16; kb++) {
          acquire(kb, true, kb >= 4 ? 16384 + 24576 : 0);
          if (lead) tma_4d_mc(dst + 16384 + rank * 12288, &P.wqkv, 32 * c, kb * 64 + kr, 0, 0, full, pol);
          if (kb >= 4) if (lead) tma_2d(dst, &P.x, kb * 64, 128 * m, full);
          if (PFD && (kb & 7) == 4 && lead) tma_pf_4d(&P.wqkv, 32 * c, pfk(kb), 2, 0);
        }
        const uint8_t* xn = g_xn + (size_t)m * 16 * 16384;
#pragma unroll 1
        for (int kb = 0; kb < 16; kb++) {
          acquire(kb, false, 16384 + 24576);
          if (lead) tma_4d_mc(dst + 16384 + rank * 12288, &P.wqkv, 32 * c, kb * 64 + kr, 2, 0, full, pol);
          if (kb == 0) { flag_wait(&g_flags[(F_XN + m) * 32], 64 * ep); TM(lead, 1); }
          if (lead) bulk_g2s(dst, xn + kb * 16384, 16384, full);
          if (PFD && (kb & 7) == 4 && lead) tma_pf_3d(&P.w1a, 0, pfk(kb), 7 * c);
        }
#pragma unroll 1
        for (int kb = 0; kb < 16; kb++) {
          acquire(kb, false, 16384 + 24576);
          if (lead) bulk_g2s(dst, xn + kb * 16384, 16384, full);
          if (lead) tma_3d_mc(dst + 16384 + rank * 12288, &P.w1a, 0, kb * 64 + kr, 7 * c, full, pol);
          if (PFD && (kb & 7) == 4 && lead) tma_pf_3d(&P.w1b, 0, pfk(kb), 7 * c + 3);
        }
#pragma unroll 1
        for (int i = 0; i < 32; i++) {
          const int kb = i & 15;
          acquire(kb, false, 32768);
          if (lead) bulk_g2s(dst, xn + kb * 16384, 16384, full);
          if (lead) tma_3d_mc(dst + 16384 + rank * 8192, &P.w1b, 0, kb * 64 + kr, 7 * c + 3 + (i >> 4) * 2, full, pol);
          if (PFD && (kb & 7) == 4 && lead) {
            if (i < 16) tma_pf_3d(&P.w1b, 0, pfk(kb), 7 * c + 5);
            else tma_pf_3d(&P.w2, 0, (7 * (m >> 1) + (kb >> 3)) * 64 + kr, 2 * c);
          }
        }
        const uint8_t* hb = g_h + (size_t)m * 56 * 16384;
        const uint8_t* ob = g_o + (size_t)m * 32 * 8192;
        int pos = 0;
        auto out_h = [&](int n, int hk, int run, int skip, const unsigned* flag) {
          int cnt = 0;
#pragma unroll 1
          for (int i = 0; i < n; i++, pos++) {
            acquire(pos, false, 32768);
            if (lead) tma_3d_mc(dst + 16384 + rank * 8192, &P.w2, 0, hk * 64 + kr, 2 * c, full, pol);
            if (i == 0) flag_wait(flag, 16 * ep);
            if (lead) bulk_g2s(dst, hb + hk * 16384, 16384, full);
            hk++;
            if (++cnt == run) { cnt = 0; hk += skip; }
            if (PFD && (pos & 7) == 0 && pos < 40 && lead) tma_pf_3d(&P.w2, 0, (7 * (m >> 1) + 2 + (pos >> 3)) * 64 + kr, 2 * c);
            if (PFD && (pos & 15) == 4 && pos < 32 && lead) tma_pf_3d(&P.wo, 0, ((pos >> 1) - 2 + (m >> 1)) * 64 + kr, 2 * c);
          }
        };
        auto out_o = [&](int j0, int j1) {
#pragma unroll 1
          for (int j = j0; j < j1; j++, pos++) {
            acquire(pos, false, 32768);
            if (lead) tma_3d_mc(dst + 16384 + rank * 8192, &P.wo, 0, j * 64 + kr, 2 * c, full, pol);
            if ((j & 3) == 0) flag_wait(&g_flags[(F_O + m * 4 + (j >> 2)) * 32], 16 * ep);
            if (lead) bulk_g2s(dst, ob + j * 16384, 16384, full);
          }
        };
        out_h(24, 0, 3, 4, &g_flags[(F_H + m * 3 + 0) * 32]);
        out_h(16, 3, 2, 5, &g_flags[(F_H + m * 3 + 1) * 32]);
        out_o(0, 8);
        out_h(16, 5, 2, 5, &g_flags[(F_H + m * 3 + 2) * 32]);
        if (lead) { tma_pf_2d(&P.x, 128 * c, 128 * m); tma_pf_2d(&P.x, 128 * c + 64, 128 * m); }
        out_o(8, 16);
        if (lead) {
          mbar_expect_tx(bars + B_STAT * 8, 32768);
          tma_2d(sb + kKvOff, &P.x, 128 * c, 128 * m, bars + B_STAT * 8);
          tma_2d(sb + kKvOff + 16384, &P.x, 128 * c + 64, 128 * m, bars + B_STAT * 8);
        }
      } else if (warp == 1) {
        flag_wait(&g_flags[(F_XN + m) * 32], 64 * ep);
        if (lead) mbar_expect_tx(bars + B_STAT * 8, 1024 + 1536);
        if (lead) bulk_g2s(sb + kQOff + 8192, g_stat + m * 128, 1024, bars + B_STAT * 8);
        uint32_t ph = 1, full = bars + B_KVFULL * 8, dst = sb + kKvOff + rank * 4096;
        const uint8_t* src = g_kv + (size_t)c * 32 * 8192 + rank * 4096;
#pragma unroll 1
        for (int g = 0; g <= 128; g++) {
          if ((g & 31) == 0 && g < 128) {
            const int u = g >> 5, head = 8 * u + c;
            flag_wait(&g_flags[(F_KV + head) * 32], 32 * ep);
            TM(lead, 2 + u);
            if (u >= 2) mbar_wait_sleepy(bars + (B_QEMPTY + (u & 1)) * 8, 0);
            if (lead) mbar_expect_tx(bars + (B_QFULL + (u & 1)) * 8, 8192);
            if (lead) bulk_g2s(sb + kQOff + (u & 1) * 8192, g_q + ((size_t)head * kS + m * 128) * 64, 8192, bars + (B_QFULL + (u & 1)) * 8);
          }
          mbar_wait_sleepy(full + (B_KVEMPTY - B_KVFULL) * 8, ph);
          if (lead) mbar_expect_tx(full, 8192);
          if (lead) bulk_g2s_mc(dst, src, 4096, full);
          const int t = g + 1 - (int)rank;
          if (t > 0 && t < 128) src += (t & 31) ? 8192 : 8192 + 7 * 32 * 8192;
          full += 8;
          dst += 8192;
          if (full == bars + (B_KVFULL + kNKv) * 8) { full -= kNKv * 8; dst -= kNKv * 8192; ph ^= 1; }
        }
      } else if (lane != 0) {
      } else if (warp == 2) {
        const uint32_t st = sb + kStageOff;
        auto store_head = [&](int head, int r, int h) {
          uint8_t* kv = g_kv + ((size_t)head * 32 + 2 * m + h) * 8192;
          bulk_s2g(kv, st + (2 + r) * 8192 + h * 4096, 4096);
          bulk_s2g(kv + 4096, st + (4 + r) * 8192 + h * 4096, 4096);
          bulk_s2g(g_q + ((size_t)head * kS + m * 128 + h * 64) * 64, st + r * 8192 + h * 4096, 4096);
        };
        mbar_wait_sleepy(bars + B_GST0 * 8, 0);
        store_head(c, 0, 0);
        mbar_wait_sleepy(bars + B_GST * 8, 0);
        store_head(c, 0, 1);
        bulk_commit();
        bulk_wait_all();
        flag_add(&g_flags[(F_KV + c) * 32], 2);
        TM(true, 52);
        mbar_wait_sleepy(bars + (B_GST + 1) * 8, 0);
        store_head(8 + c, 1, 0);
        store_head(8 + c, 1, 1);
        bulk_commit();
        bulk_wait_read();
        mbar_arrive_cta(bars + (B_GEMPTY + 3) * 8, 0, 4);
        mbar_arrive_cta(bars + (B_GEMPTY + 3) * 8, 1, 4);
        bulk_wait_all();
        flag_add(&g_flags[(F_KV + 8 + c) * 32], 2);
        TM(true, 8);
#pragma unroll 1
        for (int t = 1; t < 5; t++) {
#pragma unroll 1
          for (int h = 0; h < 2; h++) {
            mbar_wait_sleepy(bars + (B_GST + h) * 8, t & 1);
            if (t < 2) {
              store_head(16 + c, 0, h);
              store_head(24 + c, 1, h);
            } else {
              const int a0 = t == 2 ? 7 * c : 7 * c + 2 * t - 3, na = t == 2 ? 3 : 2;
              for (int a = 0; a < na; a++)
                bulk_s2g(g_h + ((size_t)m * 56 + a0 + a) * 16384 + h * 8192, st + a * 16384 + h * 8192, 8192);
            }
            bulk_commit();
          }
          bulk_wait_read();
          mbar_arrive_cta(bars + (B_GEMPTY + 3) * 8, 0, 4);
          mbar_arrive_cta(bars + (B_GEMPTY + 3) * 8, 1, 4);
          bulk_wait_all();
          if (t < 2) {
            flag_add(&g_flags[(F_KV + 16 * t + c) * 32], 2);
            flag_add(&g_flags[(F_KV + 16 * t + 8 + c) * 32], 2);
          } else {
            flag_add(&g_flags[(F_H + m * 3 + t - 2) * 32], 2);
          }
          TM(true, 8 + t);
        }
#pragma unroll 1
        for (int i = 0; i < 4; i++) {
          mbar_wait(bars + (B_OUT + i) * 8, 0);
          tma_store_2d(&P.out, sb + kKvOff + (i & 1) * 16384 + (i >> 1) * 8192, 128 * c + 64 * (i & 1), 128 * m + 64 * (i >> 1));
          bulk_commit();
        }
        bulk_wait_read();
        TM(true, 13);
      } else {
        if (PREF & 1) {
          for (int i = 0; i < 6; i++) l2_prefetch(P.wqkv_p + (size_t)blockIdx.x * 49152 + i * 8192, 8192);
          for (int i = 0; i < 7; i++) l2_prefetch(P.w1_p + (size_t)blockIdx.x * 57344 + i * 8192, 8192);
        }
#pragma unroll 1
        for (int u = 0; u < 4; u++) {
          for (int w = 0; w < 2; w++) {
            mbar_wait_sleepy(bars + (B_AST + w * 2 + (u & 1)) * 8, u >> 1);
            bulk_s2g(g_o + ((size_t)m * 32 + 8 * u + c) * 8192 + w * 4096, sb + kQOff + (u & 1) * 8192 + w * 4096, 4096);
            bulk_commit();
          }
          bulk_wait_read();
          mbar_arrive(bars + (B_QEMPTY + (u & 1)) * 8);
          bulk_wait_all();
          flag_add(&g_flags[(F_O + m * 4 + u) * 32], 2);
          TM(true, 14 + u);
          if ((PREF & 2) && u == 0) {
            for (int i = 0; i < 7; i++) l2_prefetch(P.w2_p + (size_t)blockIdx.x * 57344 + i * 8192, 8192);
            for (int i = 0; i < 2; i++) l2_prefetch(P.wo_p + (size_t)blockIdx.x * 16384 + i * 8192, 8192);
          }
        }
      }
    }
    __syncwarp();
  } else if (warp < 8) {
    asm volatile("setmaxnreg.inc.sync.aligned.u32 240;\n");
    cluster_wait();
    const int w = warp & 3;
    GemmState g;
    g.lo0 = (sb & 0x3FFFF) >> 4;
    asm volatile("" : "+r"(g.lo0));
    g.lo0 = __shfl_sync(~0u, g.lo0, 0);
    g.bars = bars;
    g.rel_addr = mapa(bars + B_GEMPTY * 8, lane & 1);
    g.rel_lane = lane < 2;
    g.phases = 0; g.r3 = 0; g.s = 0; g.twait = 0;
    const BFmt fq = {2048, desc_hi(512, 2), 1024 >> 4, 12288 >> 4};
    const BFmt f192 = {4096, desc_hi(1024, 1), 2048 >> 4, 12288 >> 4};
    const BFmt f128 = {4096, desc_hi(1024, 1), 2048 >> 4, 8192 >> 4};
    const uint32_t srow = w * 16 + (lane & 7) + ((lane >> 3) & 1) * 8, scol = lane >> 4;
    const uint32_t st = sb + kStageOff;
    const uint32_t gst0 = bars + B_GST * 8, gst1 = gst0 + 8;
    const uint32_t b64 = st + srow * 64, sw64 = (srow >> 1) & 3, b128 = srow * 128, sw128 = srow & 7;
    float d0[96], d1[96], cs[6] = {0.f, 0.f, 0.f, 0.f, 0.f, 0.f};
#pragma unroll
    for (int i = 0; i < 96; i++) { d0[i] = 0.f; d1[i] = 0.f; }
    tile_first(d0, d1, cs, sb, rank, g, fq);
    const uint32_t csb = sb + kQOff + 8192 + 1024;
    {
      const uint32_t cs_dst = mapa(csb + rank * 768 + (8 * w + (lane >> 2)) * 4, lane & 1), cs_bar = mapa(bars + B_STAT * 8, lane & 1);
#pragma unroll
      for (int i = 0; i < 6; i++) cs[i] += __shfl_xor_sync(~0u, cs[i], 1);
#pragma unroll
      for (int i = 0; i < 6; i++) cs[i] += __shfl_xor_sync(~0u, cs[i], 2);
      if ((lane & 3) < 2) {
#pragma unroll
        for (int i = 0; i < 6; i++)
          asm volatile("st.async.weak.shared::cluster.mbarrier::complete_tx::bytes.b32 [%0], %1, [%2];\n" ::"r"(cs_dst + i * 128),
                       "r"(__float_as_uint(cs[i])), "r"(cs_bar)
                       : "memory");
      }
    }
    mbar_wait(bars + B_STAT * 8, 0);
    if (threadIdx.x < 128 + 96) {
      const uint32_t a = csb + (threadIdx.x - 128) * 8;
      float x0, x1, y0, y1;
      asm volatile("ld.shared.v2.f32 {%0, %1}, [%2];\n" : "=f"(x0), "=f"(x1) : "r"(a));
      asm volatile("ld.shared.v2.f32 {%0, %1}, [%2];\n" : "=f"(y0), "=f"(y1) : "r"(a + 768));
      asm volatile("st.shared.v2.f32 [%0], {%1, %2};\n" ::"r"(a), "f"(x0 + y0), "f"(x1 + y1) : "memory");
    }
    float2 sv[4];
#pragma unroll
    for (int i = 0; i < 4; i++)
      asm volatile("ld.shared.v2.f32 {%0, %1}, [%2];\n" : "=f"(sv[i].x), "=f"(sv[i].y)
                   : "r"(sb + kQOff + 8192 + ((i >> 1) * 64 + w * 16 + (lane >> 2) + (i & 1) * 8) * 8));
    wgmma_wait<1>();
    fence_regs(d0);
    TM(threadIdx.x == 128, 20); TPUT(threadIdx.x == 128, 41, clk32());
    named_sync(1);
    epi_qkv_ln<0>(d0, csb + (lane & 3) * 8, sv[0], sv[1], b64, sw64, scol);
    epi_publish(bars + B_GST0 * 8, lane);
    epi_qkv_ln<1>(d0, csb + (lane & 3) * 8, sv[0], sv[1], b64, sw64, scol);
    tile_drain(d1, g);
    tile_head<192>(d0, g, fq);
    epi_qkv_ln<0>(d1, csb + (lane & 3) * 8, sv[2], sv[3], b64 + 4096, sw64, scol);
    epi_publish(gst0, lane);
    epi_qkv_ln<1>(d1, csb + (lane & 3) * 8, sv[2], sv[3], b64 + 4096, sw64, scol);
    epi_publish(gst1, lane);
    TM(threadIdx.x == 128, 26);
    tile_body<192, 16, GD192, false>(d0, d1, g, fq);
    TM(threadIdx.x == 128, 21);
    named_sync(1);
    epi_qkv<12, 4>(d0, b64, sw64, scol);
    epi_publish(gst0, lane);
    tile_drain(d1, g);
    tile_head<192>(d0, g, f192);
    epi_qkv<12, 4>(d1, b64 + 4096, sw64, scol);
    epi_publish(gst1, lane);
    TM(threadIdx.x == 128, 27);
    tile_body<192, 16, GD192, false>(d0, d1, g, f192);
    TM(threadIdx.x == 128, 22);
    named_sync(1);
    epi_relu<0, 12>(d0, st + b128, sw128, scol);
    epi_publish(gst0, lane);
    tile_drain(d1, g);
    tile_head<128>(d0, g, f128);
    epi_relu<0, 12>(d1, st + 8192 + b128, sw128, scol);
    epi_publish(gst1, lane);
#pragma unroll
    for (int t = 3; t < 5; t++) {
      tile_body<128, 16, GD128, false>(d0, d1, g, f128);
      TM(threadIdx.x == 128, 20 + t); TPUT(threadIdx.x == 128 && t == 4, 63, clk32());
      named_sync(1);
      epi_relu<0, 8>(d0, st + b128, sw128, scol);
      epi_publish(gst0, lane);
      tile_drain(d1, g);
      tile_head<128>(d0, g, f128);
      epi_relu<0, 8>(d1, st + 8192 + b128, sw128, scol);
      epi_publish(gst1, lane);
    }
    tile_body<128, 72, GDOUT, true>(d0, d1, g, f128);
    TM(threadIdx.x == 128, 25); TPUT(threadIdx.x == 128, 62, clk32());
    mbar_wait(bars + B_STAT * 8, 1);
    epi_out<0>(d0, sb + kKvOff + b128, sw128, scol);
    epi_publish(bars + (B_OUT + 0) * 8, lane);
    epi_out<1>(d0, sb + kKvOff + b128, sw128, scol);
    epi_publish(bars + (B_OUT + 1) * 8, lane);
    wgmma_wait<0>();
    fence_regs(d1);
    epi_out<0>(d1, sb + kKvOff + 8192 + b128, sw128, scol);
    epi_publish(bars + (B_OUT + 2) * 8, lane);
    epi_out<1>(d1, sb + kKvOff + 8192 + b128, sw128, scol);
    epi_publish(bars + (B_OUT + 3) * 8, lane);
  } else {
    asm volatile("setmaxnreg.dec.sync.aligned.u32 120;\n");
    {
      const int r0 = c * 16 + (warp - 8) * 2;
      const uint32_t lnbuf = sb + kKvOff + (warp - 8) * 4096;
      const uint32_t statbuf = sb + kKvOff + 32768 + (warp - 8) * 16;
      uint4 v[2][4];
#pragma unroll
      for (int i = 0; i < 2; i++)
#pragma unroll
        for (int j = 0; j < 4; j++)
          v[i][j] = __ldg(reinterpret_cast<const uint4*>(P.xptr + (size_t)(m * 128 + r0 + i) * kD) + lane + 32 * j);
      TM(threadIdx.x == 256, 56);
#pragma unroll
      for (int i = 0; i < 2; i++) {
        float f[32];
#pragma unroll
        for (int j = 0; j < 4; j++) {
          f[8 * j] = bf_lo(v[i][j].x); f[8 * j + 1] = bf_hi(v[i][j].x); f[8 * j + 2] = bf_lo(v[i][j].y); f[8 * j + 3] = bf_hi(v[i][j].y);
          f[8 * j + 4] = bf_lo(v[i][j].z); f[8 * j + 5] = bf_hi(v[i][j].z); f[8 * j + 6] = bf_lo(v[i][j].w); f[8 * j + 7] = bf_hi(v[i][j].w);
        }
        float sum = 0.f;
#pragma unroll
        for (int j = 0; j < 32; j++) sum += f[j];
#pragma unroll
        for (int o = 16; o; o >>= 1) sum += __shfl_xor_sync(~0u, sum, o);
        const float mean = sum * (1.f / kD);
        TM(threadIdx.x == 256 && i == 0 && mean != 123.f, 57);
        float sq = 0.f;
#pragma unroll
        for (int j = 0; j < 32; j++) { const float dlt = f[j] - mean; sq = fmaf(dlt, dlt, sq); }
#pragma unroll
        for (int o = 16; o; o >>= 1) sq += __shfl_xor_sync(~0u, sq, o);
        const float mb = bf_round(mean);
        const float den = bf_round(sqrtf(bf_round(bf_round(sq * (1.f / kD)) + 1e-5f)));
        const float inv = 1.f / den;
        const int r = r0 + i;
        if (lane == 0) asm volatile("st.shared.v2.f32 [%0], {%1, %2};\n" ::"r"(statbuf + i * 8), "f"(mb), "f"(inv) : "memory");
#pragma unroll
        for (int j = 0; j < 4; j++) {
          uint4 o;
          uint32_t dd[4];
#pragma unroll
          for (int e = 0; e < 4; e++) {
            const uint32_t t = pack_bf16(f[8 * j + 2 * e] - mb, f[8 * j + 2 * e + 1] - mb);
            dd[e] = pack_bf16(bf_lo(t) * inv, bf_hi(t) * inv);
          }
          o.x = dd[0]; o.y = dd[1]; o.z = dd[2]; o.w = dd[3];
          const int ch = lane + 32 * j;
          asm volatile("st.shared.v4.b32 [%0], {%1, %2, %3, %4};\n" ::"r"(lnbuf + (ch >> 3) * 256 + i * 128 + (((ch & 7) ^ (r & 7)) << 4)),
                       "r"(o.x), "r"(o.y), "r"(o.z), "r"(o.w)
                       : "memory");
        }
      }
      TM(threadIdx.x == 256, 58);
      fence_async_smem();
      __syncwarp();
      if (lane < 17) {
        if (lane < 16) bulk_s2g(g_xn + ((size_t)(m * 16 + lane) * 128 + r0) * 128, lnbuf + lane * 256, 256);
        else bulk_s2g(g_stat + m * 128 + r0, statbuf, 16);
        bulk_commit();
        bulk_wait_all();
      }
      __syncwarp();
      if (lane == 0) flag_add(&g_flags[(F_XN + m) * 32], 1);
      TM(threadIdx.x == 256, 59);
    }
    cluster_wait();
    const int aw = (warp - 8) >> 2, w = warp & 3;
    const bool rel_lane = lane < 2;
    const uint32_t rel_addr = mapa(bars + B_KVEMPTY * 8, lane & 1);
    constexpr int NO = ONES ? 20 : 16;
    float s[32], o[NO];
    uint32_t pa[16], pb[16];
#pragma unroll
    for (int i = 0; i < 16; i++) { pa[i] = 0u; pb[i] = 0u; }
#pragma unroll
    for (int i = 0; i < NO; i++) o[i] = 0.f;
#pragma unroll
    for (int i = 0; i < 32; i++) s[i] = 0.f;
    float l0 = 0.f, l1 = 0.f, lp0 = 0.f, lp1 = 0.f;
    const uint32_t hi64 = desc_hi(512, 2);
    const uint32_t kv_lo0 = desc_lo(sb + kKvOff, 16);
    uint32_t st = 0, ph = 0, q_lo = 0;
    uint32_t rel_prev = rel_addr;
    bool ready = false, pend = false;
    const uint32_t v_lo0 = desc_lo(sb + kKvOff + 4096, kOnesOff - kKvOff - 4096);
    auto issue_pv = [&](uint32_t (&p)[16], int acc) {
      const uint32_t v_lo = v_lo0 + st * (512u - (512u << 16));
      wgmma_rs_n40<1>(o, p[0], p[1], p[2], p[3], mk_desc(v_lo, hi64), acc);
      wgmma_rs_n40<1>(o, p[4], p[5], p[6], p[7], mk_desc(v_lo + (64u - (64u << 16)), hi64), 1);
      wgmma_rs_n40<1>(o, p[8], p[9], p[10], p[11], mk_desc(v_lo + (128u - (128u << 16)), hi64), 1);
      wgmma_rs_n40<1>(o, p[12], p[13], p[14], p[15], mk_desc(v_lo + (192u - (192u << 16)), hi64), 1);
    };
    auto issue_qk = [&]() {
      const uint32_t k_lo = kv_lo0 + st * 512;
      wgmma_ss_n64<0>(s, mk_desc(q_lo, hi64), mk_desc(k_lo, hi64), 0);
      wgmma_ss_n64<0>(s, mk_desc(q_lo + 2, hi64), mk_desc(k_lo + 2, hi64), 1);
    };
    auto softmax_tile = [&](uint32_t (&p)[16]) {
#pragma unroll
      for (int i = 0; i < 8; i++) {
        const float e0 = ex2(s[4 * i]), e1 = ex2(s[4 * i + 1]), e2 = ex2(s[4 * i + 2]), e3 = ex2(s[4 * i + 3]);
        if (!ONES) { l0 += e0 + e1; l1 += e2 + e3; }
        p[2 * i] = pack_bf16(e0, e1); p[2 * i + 1] = pack_bf16(e2, e3);
      }
    };
    auto advance = [&]() {
      rel_prev = rel_addr + st * 8;
      if (++st == kNKv) { st = 0; ph ^= 1; }
      ready = mbar_test(bars + (B_KVFULL + st) * 8, ph);
    };
    auto finish = [&](int u) {
      const uint32_t ob = sb + kQOff + (u & 1) * 8192 + aw * 4096;
      const float t0 = o[16], t1 = o[18];
      bool ok = t0 >= 8.271806e-25f && t0 <= 1.2676506e30f && t1 >= 8.271806e-25f && t1 <= 1.2676506e30f;
#pragma unroll
      for (int i = 0; i < 16; i++) ok = ok && (fabsf(o[i]) <= 3.0e38f);
      const float i0 = 1.f / t0, i1 = 1.f / t1;
      uint32_t r[8];
#pragma unroll
      for (int i = 0; i < 4; i++) {
        r[2 * i] = pack_bf16(o[4 * i] * i0, o[4 * i + 1] * i0);
        r[2 * i + 1] = pack_bf16(o[4 * i + 2] * i1, o[4 * i + 3] * i1);
      }
      if (__any_sync(~0u, !ok)) {
        float e[16];
        attn_exact(e, ob + w * 1024, g_kv + (size_t)(8 * u + c) * 32 * 8192);
#pragma unroll
        for (int i = 0; i < 8; i++) r[i] = pack_bf16(e[2 * i], e[2 * i + 1]);
      }
      __syncwarp();
      const uint32_t srow = w * 16 + (lane & 7) + ((lane >> 3) & 1) * 8, scol = lane >> 4;
      const uint32_t base = ob + srow * 64, sw = (srow >> 1) & 3;
      stsm4(base + ((scol ^ sw) << 4), r[0], r[1], r[2], r[3]);
      stsm4(base + (((2 + scol) ^ sw) << 4), r[4], r[5], r[6], r[7]);
      epi_publish(bars + (B_AST + aw * 2 + (u & 1)) * 8, lane);
      TM(threadIdx.x == 256, 31 + u);
      TPUT(threadIdx.x == 256, 47 + u, clk32());
    };
    auto issue = [&](uint32_t (&pin)[16], uint32_t (&pout)[16], int acc) {
      fence_regs(s); fence_regs(o); fence_regs(pin); fence_regs(pout);
      wgmma_fence();
      issue_qk();
      wgmma_commit();
      issue_pv(pin, acc);
      wgmma_commit();
      mbar_arrive_cluster_if(rel_prev, rel_lane && pend);
      pend = true;
      wgmma_wait<1>();
      fence_regs(s);
      advance();
    };
    mbar_wait(bars + B_KVFULL * 8, 0);
#pragma unroll 1
    for (int it = 0; it <= 64; it++) {
      const bool bnd = (it & 15) == 0;
      const int u = it >> 4;
      if (bnd) {
        q_lo = desc_lo(sb + kQOff + (u & 1) * 8192 + aw * 4096, 16);
        if (u < 4) mbar_wait(bars + (B_QFULL + (u & 1)) * 8, u >> 1);
        lp0 = l0; lp1 = l1; l0 = 0.f; l1 = 0.f;
      }
      issue(pb, pa, 1);
      softmax_tile(pa);
      if (!ready && it < 64) mbar_wait(bars + (B_KVFULL + st) * 8, ph);
      wgmma_wait<0>();
      if (bnd) {
        fence_regs(o);
        if (it > 0) finish(u - 1);
        if (it == 64) break;
      }
      issue(pa, pb, !bnd);
      softmax_tile(pb);
      if (!ready) mbar_wait(bars + (B_KVFULL + st) * 8, ph);
      wgmma_wait<0>();
    }
  }

  cluster_arrive();
  cluster_wait();
  TM(threadIdx.x == 0, 40);
  TPUT(threadIdx.x == 0, 61, clk32());
  if (blockIdx.x == 0 && threadIdx.x == 0) flag_add(&g_flags[F_EPOCH * 32], 1);
}

typedef CUresult (*EncodeFn)(CUtensorMap*, CUtensorMapDataType, cuuint32_t, void*, const cuuint64_t*, const cuuint64_t*,
                             const cuuint32_t*, const cuuint32_t*, CUtensorMapInterleave, CUtensorMapSwizzle,
                             CUtensorMapL2promotion, CUtensorMapFloatOOBfill);

void encode(EncodeFn fn, CUtensorMap* map, const void* base, int rank, const cuuint64_t* dims, const cuuint64_t* strides,
            const cuuint32_t* box, CUtensorMapSwizzle sw) {
  const cuuint32_t es[5] = {1, 1, 1, 1, 1};
  fn(map, CU_TENSOR_MAP_DATA_TYPE_BFLOAT16, rank, const_cast<void*>(base), dims, strides, box, es,
     CU_TENSOR_MAP_INTERLEAVE_NONE, sw, CU_TENSOR_MAP_L2_PROMOTION_L2_256B, CU_TENSOR_MAP_FLOAT_OOB_FILL_NONE);
}

}

extern "C" void kernel_launch(void* const* d_in, const int* in_sizes, int n_in, void* d_out, int out_size) {
  (void)in_sizes; (void)n_in; (void)out_size;
  static Params P;
  static const void* key[6] = {nullptr, nullptr, nullptr, nullptr, nullptr, nullptr};
  const void* cur[6] = {d_in[0], d_in[1], d_in[2], d_in[4], d_in[5], d_out};
  bool same = true;
  for (int i = 0; i < 6; i++) same = same && key[i] == cur[i];
  if (!same) {
    void* fn = nullptr;
    cudaDriverEntryPointQueryResult q;
    cudaGetDriverEntryPoint("cuTensorMapEncodeTiled", &fn, cudaEnableDefault, &q);
    EncodeFn enc = (EncodeFn)fn;
    {
      const cuuint64_t d[4] = {256, 1024, 4, 3}, s[3] = {6144, 512, 2048};
      const cuuint32_t b[4] = {32, 32, 2, 3};
      encode(enc, &P.wqkv, d_in[1], 4, d, s, b, CU_TENSOR_MAP_SWIZZLE_64B);
    }
    {
      const cuuint64_t d[3] = {64, 1024, 56}, s[2] = {kDff * 2, 128};
      const cuuint32_t b3[3] = {64, 32, 3}, b2[3] = {64, 32, 2};
      encode(enc, &P.w1a, d_in[4], 3, d, s, b3, CU_TENSOR_MAP_SWIZZLE_128B);
      encode(enc, &P.w1b, d_in[4], 3, d, s, b2, CU_TENSOR_MAP_SWIZZLE_128B);
    }
    {
      const cuuint64_t d2[3] = {64, kDff, 16}, d1[3] = {64, kD, 16}, s[2] = {kD * 2, 128};
      const cuuint32_t b[3] = {64, 32, 2};
      encode(enc, &P.w2, d_in[5], 3, d2, s, b, CU_TENSOR_MAP_SWIZZLE_128B);
      encode(enc, &P.wo, d_in[2], 3, d1, s, b, CU_TENSOR_MAP_SWIZZLE_128B);
    }
    {
      const cuuint64_t d[2] = {kD, kS}, s[1] = {kD * 2};
      const cuuint32_t bx[2] = {64, 128}, bo[2] = {64, 64};
      encode(enc, &P.x, d_in[0], 2, d, s, bx, CU_TENSOR_MAP_SWIZZLE_128B);
      encode(enc, &P.out, d_out, 2, d, s, bo, CU_TENSOR_MAP_SWIZZLE_128B);
    }
    P.xptr = (const __nv_bfloat16*)d_in[0];
    P.wqkv_p = (const uint8_t*)d_in[1];
    P.wo_p = (const uint8_t*)d_in[2];
    P.w1_p = (const uint8_t*)d_in[4];
    P.w2_p = (const uint8_t*)d_in[5];
    cudaFuncSetAttribute(fused_block_kernel, cudaFuncAttributeMaxDynamicSharedMemorySize, kSmemBytes);
    for (int i = 0; i < 6; i++) key[i] = cur[i];
  }
  fused_block_kernel<<<kCtas, kThreads, kSmemBytes>>>(P);
}
```

```cpp
#include <cuda_runtime.h>
#include <cuda_bf16.h>
#include <cuda.h>
#include <stdint.h>

namespace {

constexpr int kS = 2048, kD = 1024, kDff = 3584;
constexpr int kThreads = 512;
constexpr int kCtas = 128;
constexpr int kDepth192 = 11, kDepth128 = 21;

constexpr uint32_t kSlot = 40960;
constexpr uint32_t kStageOff = 3 * kSlot;
constexpr uint32_t kKvOff = 4 * kSlot + 8192;
constexpr uint32_t kNKv = 5;
constexpr uint32_t kQOff = kKvOff + kNKv * 8192;
constexpr uint32_t kCsOff = kQOff + 8192 + 1024;
constexpr uint32_t kBarOff = kQOff + 2 * 8192;
constexpr uint32_t kOnesOff = kBarOff + 512;
constexpr uint32_t kSmemBytes = kOnesOff + 1024 + 1024;
constexpr uint32_t B_GFULL = 0, B_GEMPTY = 4, B_KVFULL = 8, B_KVEMPTY = 13, B_QFULL = 18, B_QEMPTY = 20, B_GST = 22,
                   B_AST = 24, B_STAT = 28, B_GST0 = 29, B_OUT = 30, B_LN = 34;

__device__ __align__(1024) uint8_t g_kv[32 * 32 * 8192];
__device__ __align__(1024) uint8_t g_h[16 * 56 * 16384];
__device__ __align__(1024) uint8_t g_o[16 * 32 * 8192];
__device__ __align__(1024) float2 g_stat[2048];
constexpr int F_XN = 0, F_KV = 16, F_H = 48, F_O = 96, F_EPOCH = 160, F_COUNT = 161;
__device__ unsigned g_flags[F_COUNT * 32];

__device__ __forceinline__ uint32_t smem_u32(const void* p) { return (uint32_t)__cvta_generic_to_shared(p); }
__device__ __forceinline__ void wgmma_fence() { asm volatile("wgmma.fence.sync.aligned;\n" ::: "memory"); }
__device__ __forceinline__ void wgmma_commit() { asm volatile("wgmma.commit_group.sync.aligned;\n" ::: "memory"); }
template <int N>
__device__ __forceinline__ void wgmma_wait() { asm volatile("wgmma.wait_group.sync.aligned %0;\n" ::"n"(N) : "memory"); }
template <int N>
__device__ __forceinline__ void fence_regs(float (&r)[N]) {
#pragma unroll
  for (int i = 0; i < N; i++) asm volatile("" : "+f"(r[i])::"memory");
}
template <int N>
__device__ __forceinline__ void fence_regs(uint32_t (&r)[N]) {
#pragma unroll
  for (int i = 0; i < N; i++) asm volatile("" : "+r"(r[i])::"memory");
}
__device__ __forceinline__ uint64_t mk_desc(uint32_t lo, uint32_t hi) { return ((uint64_t)hi << 32) | lo; }
__host__ __device__ constexpr uint32_t desc_hi(uint32_t sbo, uint32_t swz) { return (sbo >> 4) | (swz << 30); }
__device__ __forceinline__ uint32_t desc_lo(uint32_t addr, uint32_t lbo) { return ((addr & 0x3FFFF) >> 4) | ((lbo >> 4) << 16); }

__device__ __forceinline__ void mbar_init(uint32_t bar, uint32_t cnt) {
  asm volatile("mbarrier.init.shared::cta.b64 [%0], %1;\n" ::"r"(bar), "r"(cnt) : "memory");
}
__device__ __forceinline__ void mbar_expect_tx(uint32_t bar, uint32_t bytes) {
  asm volatile("mbarrier.arrive.expect_tx.shared::cta.b64 _, [%0], %1;\n" ::"r"(bar), "r"(bytes) : "memory");
}
__device__ __forceinline__ void mbar_arrive(uint32_t bar) {
  asm volatile("mbarrier.arrive.shared::cta.b64 _, [%0];\n" ::"r"(bar) : "memory");
}
__device__ __forceinline__ void mbar_arrive_cta(uint32_t bar, uint32_t cta, uint32_t cnt) {
  asm volatile(
      "{\n.reg .b32 ra;\nmapa.shared::cluster.u32 ra, %0, %1;\nmbarrier.arrive.shared::cluster.b64 _, [ra], %2;\n}\n" ::"r"(bar),
      "r"(cta), "r"(cnt)
      : "memory");
}
__device__ __forceinline__ bool mbar_test(uint32_t bar, uint32_t parity) {
  uint32_t ok;
  asm volatile("{\n.reg .pred p;\nmbarrier.test_wait.parity.shared::cta.b64 p, [%1], %2;\nselp.u32 %0, 1, 0, p;\n}\n"
               : "=r"(ok)
               : "r"(bar), "r"(parity)
               : "memory");
  return ok;
}
__device__ __forceinline__ void mbar_wait(uint32_t bar, uint32_t parity) {
  asm volatile(
      "{\n.reg .pred p, q;\n.reg .u32 it;\nmov.u32 it, 0;\n"
      "LW_%=:\n"
      "mbarrier.try_wait.parity.shared::cta.b64 p, [%0], %1;\n"
      "@p bra LD_%=;\n"
      "add.u32 it, it, 1;\n"
      "setp.lt.u32 q, it, 0x80000;\n"
      "@q bra LW_%=;\n"
      "trap;\n"
      "LD_%=:\n}\n" ::"r"(bar), "r"(parity) : "memory");
}
__device__ __forceinline__ uint32_t mapa(uint32_t addr, uint32_t cta) {
  uint32_t r;
  asm("mapa.shared::cluster.u32 %0, %1, %2;\n" : "=r"(r) : "r"(addr), "r"(cta));
  return r;
}
__device__ __forceinline__ void mbar_arrive_cluster_if(uint32_t addr, bool pred) {
  asm volatile("{\n.reg .pred p;\nsetp.ne.u32 p, %1, 0;\n@p mbarrier.arrive.shared::cluster.b64 _, [%0];\n}\n" ::"r"(addr),
               "r"((uint32_t)pred)
               : "memory");
}
__device__ __forceinline__ void flag_wait(const unsigned* f, unsigned target) {
  uint32_t it = 0;
#pragma unroll 1
  while (true) {
    unsigned v;
    asm volatile("ld.relaxed.gpu.global.u32 %0, [%1];\n" : "=r"(v) : "l"(f) : "memory");
    if ((int)(v - target) >= 0) break;
    if (++it > (1u << 22)) asm volatile("trap;");
  }
  asm volatile("{\n.reg .u32 v;\nld.acquire.gpu.global.u32 v, [%0];\n}\n" ::"l"(f) : "memory");
  asm volatile("fence.proxy.async.global;\n" ::: "memory");
}
__device__ __forceinline__ void flag_add(unsigned* f, unsigned v) {
  asm volatile("red.relaxed.gpu.global.add.u32 [%0], %1;\n" ::"l"(f), "r"(v) : "memory");
}
__device__ __forceinline__ bool elect_one() {
  uint32_t p;
  asm volatile("{\n.reg .pred P;\nelect.sync _|P, 0xffffffff;\nselp.u32 %0, 1, 0, P;\n}\n" : "=r"(p));
  return p;
}
__device__ __forceinline__ void bulk_g2s(uint32_t dst, const void* src, uint32_t bytes, uint32_t bar) {
  asm volatile("cp.async.bulk.shared::cluster.global.mbarrier::complete_tx::bytes [%0], [%1], %2, [%3];\n" ::"r"(dst),
               "l"(src), "r"(bytes), "r"(bar)
               : "memory");
}
__device__ __forceinline__ void bulk_g2s_mc(uint32_t dst, const void* src, uint32_t bytes, uint32_t bar) {
  asm volatile(
      "cp.async.bulk.shared::cluster.global.mbarrier::complete_tx::bytes.multicast::cluster [%0], [%1], %2, [%3], %4;\n" ::"r"(dst),
      "l"(src), "r"(bytes), "r"(bar), "h"((uint16_t)3)
      : "memory");
}
__device__ __forceinline__ void bulk_s2g(void* dst, uint32_t src, uint32_t bytes) {
  asm volatile("cp.async.bulk.global.shared::cta.bulk_group [%0], [%1], %2;\n" ::"l"(dst), "r"(src), "r"(bytes) : "memory");
}
__device__ __forceinline__ void bulk_commit() { asm volatile("cp.async.bulk.commit_group;\n" ::: "memory"); }
__device__ __forceinline__ void bulk_wait_read() { asm volatile("cp.async.bulk.wait_group.read 0;\n" ::: "memory"); }
__device__ __forceinline__ void bulk_s2g_paced(void* dst, uint32_t src, uint32_t bytes) {
  bulk_s2g(dst, src, bytes);
  bulk_commit();
  bulk_wait_read();
}
__device__ __forceinline__ void bulk_wait_all() { asm volatile("cp.async.bulk.wait_group 0;\n" ::: "memory"); }
__device__ __forceinline__ void tma_2d(uint32_t dst, const CUtensorMap* m, int c0, int c1, uint32_t bar) {
  asm volatile(
      "cp.async.bulk.tensor.2d.shared::cluster.global.mbarrier::complete_tx::bytes [%0], [%1, {%3, %4}], [%2];\n" ::"r"(dst),
      "l"((uint64_t)m), "r"(bar), "r"(c0), "r"(c1)
      : "memory");
}
__device__ __forceinline__ void tma_4d(uint32_t dst, const CUtensorMap* m, int c0, int c1, int c2, int c3, uint32_t bar) {
  asm volatile(
      "cp.async.bulk.tensor.4d.shared::cluster.global.mbarrier::complete_tx::bytes [%0], [%1, {%3, %4, %5, %6}], [%2];\n" ::"r"(dst),
      "l"((uint64_t)m), "r"(bar), "r"(c0), "r"(c1), "r"(c2), "r"(c3)
      : "memory");
}
__device__ __forceinline__ void tma_3d_mc(uint32_t dst, const CUtensorMap* m, int c0, int c1, int c2, uint32_t bar) {
  asm volatile(
      "cp.async.bulk.tensor.3d.shared::cluster.global.mbarrier::complete_tx::bytes.multicast::cluster [%0], [%1, {%3, %4, %5}], "
      "[%2], %6;\n" ::"r"(dst),
      "l"((uint64_t)m), "r"(bar), "r"(c0), "r"(c1), "r"(c2), "h"((uint16_t)3)
      : "memory");
}
__device__ __forceinline__ void tma_4d_mc(uint32_t dst, const CUtensorMap* m, int c0, int c1, int c2, int c3, uint32_t bar) {
  asm volatile(
      "cp.async.bulk.tensor.4d.shared::cluster.global.mbarrier::complete_tx::bytes.multicast::cluster [%0], [%1, {%3, %4, %5, "
      "%6}], [%2], %7;\n" ::"r"(dst),
      "l"((uint64_t)m), "r"(bar), "r"(c0), "r"(c1), "r"(c2), "r"(c3), "h"((uint16_t)3)
      : "memory");
}
__device__ __forceinline__ void tma_pf_2d(const CUtensorMap* m, int c0, int c1) {
  asm volatile("cp.async.bulk.prefetch.tensor.2d.L2.global [%0, {%1, %2}];\n" ::"l"((uint64_t)m), "r"(c0), "r"(c1) : "memory");
}
__device__ __forceinline__ void tma_store_2d(const CUtensorMap* m, uint32_t src, int c0, int c1) {
  asm volatile("cp.async.bulk.tensor.2d.global.shared::cta.bulk_group [%0, {%2, %3}], [%1];\n" ::"l"((uint64_t)m), "r"(src),
               "r"(c0), "r"(c1)
               : "memory");
}
__device__ __forceinline__ void prefetch_map(const CUtensorMap* m) {
  asm volatile("prefetch.tensormap [%0];\n" ::"l"((uint64_t)m) : "memory");
}
__device__ __forceinline__ void fence_async_smem() { asm volatile("fence.proxy.async.shared::cta;\n" ::: "memory"); }
__device__ __forceinline__ void stsm4(uint32_t addr, uint32_t a, uint32_t b, uint32_t c, uint32_t d) {
  asm volatile("stmatrix.sync.aligned.m8n8.x4.shared.b16 [%0], {%1, %2, %3, %4};\n" ::"r"(addr), "r"(a), "r"(b), "r"(c), "r"(d)
               : "memory");
}
__device__ __forceinline__ void ldsm4(uint32_t addr, uint32_t& a, uint32_t& b, uint32_t& c, uint32_t& d) {
  asm volatile("ldmatrix.sync.aligned.m8n8.x4.shared.b16 {%0, %1, %2, %3}, [%4];\n"
               : "=r"(a), "=r"(b), "=r"(c), "=r"(d)
               : "r"(addr)
               : "memory");
}
__device__ __forceinline__ float ex2(float x) {
  float y;
  asm("ex2.approx.ftz.f32 %0, %1;" : "=f"(y) : "f"(x));
  return y;
}
__device__ __forceinline__ uint32_t pack_bf16(float lo, float hi) {
  uint32_t r;
  asm("cvt.rn.bf16x2.f32 %0, %1, %2;" : "=r"(r) : "f"(hi), "f"(lo));
  return r;
}
__device__ __forceinline__ uint32_t pack_bf16_relu(float lo, float hi) {
  uint32_t r;
  asm("cvt.rn.relu.bf16x2.f32 %0, %1, %2;" : "=r"(r) : "f"(hi), "f"(lo));
  return r;
}
__device__ __forceinline__ float bf_lo(uint32_t v) {
  uint32_t r;
  asm("prmt.b32 %0, %1, 0, 0x1044;" : "=r"(r) : "r"(v));
  return __uint_as_float(r);
}
__device__ __forceinline__ float bf_hi(uint32_t v) { return __uint_as_float(v & 0xffff0000u); }
__device__ __forceinline__ float bf_round(float x) { return __bfloat162float(__float2bfloat16_rn(x)); }
__device__ __forceinline__ void named_sync(int id) { asm volatile("bar.sync %0, 128;\n" ::"r"(id) : "memory"); }
__device__ __forceinline__ void cluster_arrive() { asm volatile("barrier.cluster.arrive.relaxed.aligned;\n" ::: "memory"); }
__device__ __forceinline__ void cluster_wait() { asm volatile("barrier.cluster.wait.acquire.aligned;\n" ::: "memory"); }

template <int TB>
__device__ __forceinline__ void wgmma_ss_n192(float (&d)[96], uint64_t da, uint64_t db, int scale_d) {
  asm volatile(
      "{\n.reg .pred p;\nsetp.ne.b32 p, %98, 0;\n"
      "wgmma.mma_async.sync.aligned.m64n192k16.f32.bf16.bf16 {"
      "%0, %1, %2, %3, %4, %5, %6, %7, %8, %9, %10, %11, %12, %13, %14, %15, "
      "%16, %17, %18, %19, %20, %21, %22, %23, %24, %25, %26, %27, %28, %29, %30, %31, "
      "%32, %33, %34, %35, %36, %37, %38, %39, %40, %41, %42, %43, %44, %45, %46, %47, "
      "%48, %49, %50, %51, %52, %53, %54, %55, %56, %57, %58, %59, %60, %61, %62, %63, "
      "%64, %65, %66, %67, %68, %69, %70, %71, %72, %73, %74, %75, %76, %77, %78, %79, "
      "%80, %81, %82, %83, %84, %85, %86, %87, %88, %89, %90, %91, %92, %93, %94, %95}, %96, %97, p, 1, 1, 0, %99;\n}\n"
      : "+f"(d[0]), "+f"(d[1]), "+f"(d[2]), "+f"(d[3]), "+f"(d[4]), "+f"(d[5]), "+f"(d[6]), "+f"(d[7]),
        "+f"(d[8]), "+f"(d[9]), "+f"(d[10]), "+f"(d[11]), "+f"(d[12]), "+f"(d[13]), "+f"(d[14]), "+f"(d[15]),
        "+f"(d[16]), "+f"(d[17]), "+f"(d[18]), "+f"(d[19]), "+f"(d[20]), "+f"(d[21]), "+f"(d[22]), "+f"(d[23]),
        "+f"(d[24]), "+f"(d[25]), "+f"(d[26]), "+f"(d[27]), "+f"(d[28]), "+f"(d[29]), "+f"(d[30]), "+f"(d[31]),
        "+f"(d[32]), "+f"(d[33]), "+f"(d[34]), "+f"(d[35]), "+f"(d[36]), "+f"(d[37]), "+f"(d[38]), "+f"(d[39]),
        "+f"(d[40]), "+f"(d[41]), "+f"(d[42]), "+f"(d[43]), "+f"(d[44]), "+f"(d[45]), "+f"(d[46]), "+f"(d[47]),
        "+f"(d[48]), "+f"(d[49]), "+f"(d[50]), "+f"(d[51]), "+f"(d[52]), "+f"(d[53]), "+f"(d[54]), "+f"(d[55]),
        "+f"(d[56]), "+f"(d[57]), "+f"(d[58]), "+f"(d[59]), "+f"(d[60]), "+f"(d[61]), "+f"(d[62]), "+f"(d[63]),
        "+f"(d[64]), "+f"(d[65]), "+f"(d[66]), "+f"(d[67]), "+f"(d[68]), "+f"(d[69]), "+f"(d[70]), "+f"(d[71]),
        "+f"(d[72]), "+f"(d[73]), "+f"(d[74]), "+f"(d[75]), "+f"(d[76]), "+f"(d[77]), "+f"(d[78]), "+f"(d[79]),
        "+f"(d[80]), "+f"(d[81]), "+f"(d[82]), "+f"(d[83]), "+f"(d[84]), "+f"(d[85]), "+f"(d[86]), "+f"(d[87]),
        "+f"(d[88]), "+f"(d[89]), "+f"(d[90]), "+f"(d[91]), "+f"(d[92]), "+f"(d[93]), "+f"(d[94]), "+f"(d[95])
      : "l"(da), "l"(db), "r"(scale_d), "n"(TB));
}
template <int TB>
__device__ __forceinline__ void wgmma_ss_n128(float (&d)[96], uint64_t da, uint64_t db, int scale_d) {
  asm volatile(
      "{\n.reg .pred p;\nsetp.ne.b32 p, %66, 0;\n"
      "wgmma.mma_async.sync.aligned.m64n128k16.f32.bf16.bf16 {"
      "%0, %1, %2, %3, %4, %5, %6, %7, %8, %9, %10, %11, %12, %13, %14, %15, "
      "%16, %17, %18, %19, %20, %21, %22, %23, %24, %25, %26, %27, %28, %29, %30, %31, "
      "%32, %33, %34, %35, %36, %37, %38, %39, %40, %41, %42, %43, %44, %45, %46, %47, "
      "%48, %49, %50, %51, %52, %53, %54, %55, %56, %57, %58, %59, %60, %61, %62, %63}, %64, %65, p, 1, 1, 0, %67;\n}\n"
      : "+f"(d[0]), "+f"(d[1]), "+f"(d[2]), "+f"(d[3]), "+f"(d[4]), "+f"(d[5]), "+f"(d[6]), "+f"(d[7]),
        "+f"(d[8]), "+f"(d[9]), "+f"(d[10]), "+f"(d[11]), "+f"(d[12]), "+f"(d[13]), "+f"(d[14]), "+f"(d[15]),
        "+f"(d[16]), "+f"(d[17]), "+f"(d[18]), "+f"(d[19]), "+f"(d[20]), "+f"(d[21]), "+f"(d[22]), "+f"(d[23]),
        "+f"(d[24]), "+f"(d[25]), "+f"(d[26]), "+f"(d[27]), "+f"(d[28]), "+f"(d[29]), "+f"(d[30]), "+f"(d[31]),
        "+f"(d[32]), "+f"(d[33]), "+f"(d[34]), "+f"(d[35]), "+f"(d[36]), "+f"(d[37]), "+f"(d[38]), "+f"(d[39]),
        "+f"(d[40]), "+f"(d[41]), "+f"(d[42]), "+f"(d[43]), "+f"(d[44]), "+f"(d[45]), "+f"(d[46]), "+f"(d[47]),
        "+f"(d[48]), "+f"(d[49]), "+f"(d[50]), "+f"(d[51]), "+f"(d[52]), "+f"(d[53]), "+f"(d[54]), "+f"(d[55]),
        "+f"(d[56]), "+f"(d[57]), "+f"(d[58]), "+f"(d[59]), "+f"(d[60]), "+f"(d[61]), "+f"(d[62]), "+f"(d[63])
      : "l"(da), "l"(db), "r"(scale_d), "n"(TB));
}
template <int TB>
__device__ __forceinline__ void wgmma_ss_n64(float (&d)[32], uint64_t da, uint64_t db, int scale_d) {
  asm volatile(
      "{\n.reg .pred p;\nsetp.ne.b32 p, %34, 0;\n"
      "wgmma.mma_async.sync.aligned.m64n64k16.f32.bf16.bf16 {"
      "%0, %1, %2, %3, %4, %5, %6, %7, %8, %9, %10, %11, %12, %13, %14, %15, "
      "%16, %17, %18, %19, %20, %21, %22, %23, %24, %25, %26, %27, %28, %29, %30, %31}, %32, %33, p, 1, 1, 0, %35;\n}\n"
      : "+f"(d[0]), "+f"(d[1]), "+f"(d[2]), "+f"(d[3]), "+f"(d[4]), "+f"(d[5]), "+f"(d[6]), "+f"(d[7]),
        "+f"(d[8]), "+f"(d[9]), "+f"(d[10]), "+f"(d[11]), "+f"(d[12]), "+f"(d[13]), "+f"(d[14]), "+f"(d[15]),
        "+f"(d[16]), "+f"(d[17]), "+f"(d[18]), "+f"(d[19]), "+f"(d[20]), "+f"(d[21]), "+f"(d[22]), "+f"(d[23]),
        "+f"(d[24]), "+f"(d[25]), "+f"(d[26]), "+f"(d[27]), "+f"(d[28]), "+f"(d[29]), "+f"(d[30]), "+f"(d[31])
      : "l"(da), "l"(db), "r"(scale_d), "n"(TB));
}
template <int TB>
__device__ __forceinline__ void wgmma_rs_n40(float (&d)[20], uint32_t a0, uint32_t a1, uint32_t a2, uint32_t a3,
                                             uint64_t db, int scale_d) {
  asm volatile(
      "{\n.reg .pred p;\nsetp.ne.b32 p, %25, 0;\n"
      "wgmma.mma_async.sync.aligned.m64n40k16.f32.bf16.bf16 {"
      "%0, %1, %2, %3, %4, %5, %6, %7, %8, %9, %10, %11, %12, %13, %14, %15, "
      "%16, %17, %18, %19}, {%20, %21, %22, %23}, %24, p, 1, 1, %26;\n}\n"
      : "+f"(d[0]), "+f"(d[1]), "+f"(d[2]), "+f"(d[3]), "+f"(d[4]), "+f"(d[5]), "+f"(d[6]), "+f"(d[7]),
        "+f"(d[8]), "+f"(d[9]), "+f"(d[10]), "+f"(d[11]), "+f"(d[12]), "+f"(d[13]), "+f"(d[14]), "+f"(d[15]),
        "+f"(d[16]), "+f"(d[17]), "+f"(d[18]), "+f"(d[19])
      : "r"(a0), "r"(a1), "r"(a2), "r"(a3), "l"(db), "r"(scale_d), "n"(TB));
}


template <int N>
__device__ __forceinline__ void wgmma_gemm(float (&d)[96], uint64_t da, uint64_t db, int sc) {
  if constexpr (N == 192) wgmma_ss_n192<1>(d, da, db, sc);
  else wgmma_ss_n128<1>(d, da, db, sc);
}

__device__ __forceinline__ uint32_t next_slot(int pos, bool early, uint32_t& r3) {
  const bool x = (pos & 3) == 2 && (early || pos >= 6);
  const uint32_t s = x ? 3u : r3;
  r3 = x ? r3 : ((r3 == 2) ? 0u : r3 + 1);
  return s;
}
__device__ __forceinline__ bool out_kb_is_attn(int kb) { return (kb >= 40 && kb < 48) || kb >= 64; }

#define GWAIT(bar, par) do { if (!ready) mbar_wait(bar, par); } while (0)
struct GemmState {
  uint32_t lo0, bars, rel_addr;
  uint32_t phases, r3, s;
  bool rel_lane;
  int zero;
};
struct BFmt { uint32_t lbo, hi, k1, k2; };

template <int N>
__device__ __forceinline__ void mma_half(float (&d)[96], uint32_t a_lo, uint32_t a_hi, uint32_t a_k2, uint32_t b_lo, const BFmt b,
                                         int k, int sc) {
  wgmma_gemm<N>(d, mk_desc(a_lo + (k >> 1) * a_k2 + (k & 1) * 2, a_hi), mk_desc(b_lo + (k >> 1) * b.k2 + (k & 1) * b.k1, b.hi), sc);
}
template <int N>
__device__ __forceinline__ void tile_head(float (&d0)[96], GemmState& g, const BFmt b) {
  g.s = next_slot(0, false, g.r3);
  const bool ready = false;
  GWAIT(g.bars + (B_GFULL + g.s) * 8, (g.phases >> g.s) & 1);
  const uint32_t a_c = g.lo0 + (1u << 16), b_c = g.lo0 + (16384 >> 4) + ((b.lbo >> 4) << 16);
  fence_regs(d0);
  wgmma_fence();
#pragma unroll
  for (int k = 0; k < 4; k++)
    mma_half<N>(d0, a_c + g.s * (kSlot >> 4), desc_hi(1024, 1), 64 >> 4, b_c + g.s * (kSlot >> 4), b, k, k > 0 ? 1 : g.zero);
  wgmma_commit();
}
template <int N, int NKB, int DEPTH, bool OUTK, bool EARLYX, bool RELX>
__device__ __forceinline__ void tile_body(float (&d0)[96], float (&d1)[96], GemmState& g, const BFmt b) {
  constexpr int GA = DEPTH / 10, GB = DEPTH % 10, GD = 1;
  static_assert(GB == 1 && GA <= 2, "release points below assume these depths");
  const uint32_t a_c = g.lo0 + (1u << 16), b_c = g.lo0 + (16384 >> 4) + ((b.lbo >> 4) << 16);
  uint32_t s = g.s, rel, a_lo, b_lo;
  uint32_t a_hi = desc_hi(1024, 1), a_half = 8192 >> 4, a_k2 = 64 >> 4;
  bool ready;
  auto prepare = [&](int kb) {
    g.phases ^= 1u << s;
    rel = g.rel_addr + s * 8;
    s = next_slot(kb, EARLYX, g.r3);
    a_lo = a_c + s * (kSlot >> 4);
    b_lo = b_c + s * (kSlot >> 4);
    if (OUTK) {
      const bool at = out_kb_is_attn(kb);
      a_hi = at ? desc_hi(512, 2) : desc_hi(1024, 1);
      a_half = at ? 4096 >> 4 : 8192 >> 4;
      a_k2 = at ? 8192 >> 4 : 64 >> 4;
    }
    ready = mbar_test(g.bars + (B_GFULL + s) * 8, (g.phases >> s) & 1);
  };
  {
    const uint32_t ca = a_c + s * (kSlot >> 4) + (8192 >> 4), cb = b_c + s * (kSlot >> 4);
    fence_regs(d1);
    wgmma_fence();
#pragma unroll
    for (int k = 0; k < 4; k++) {
      wgmma_wait<GD>();
      mma_half<N>(d1, ca, desc_hi(1024, 1), 64 >> 4, cb, b, k, k > 0 ? 1 : g.zero);
      wgmma_commit();
      if (k == 1) prepare(1);
    }
  }
#pragma unroll 1
  for (int kb = 1; kb < NKB - (OUTK ? 2 : 1); kb++) {
    GWAIT(g.bars + (B_GFULL + s) * 8, (g.phases >> s) & 1);
    const uint32_t ca_lo = a_lo, cb_lo = b_lo, ca_hi = a_hi, ca_half = a_half, ca_k2 = a_k2, crel = rel;
    wgmma_fence();
#pragma unroll
    for (int k = 0; k < 4; k++) {
      wgmma_wait<GA>();
      mma_half<N>(d0, ca_lo, ca_hi, ca_k2, cb_lo, b, k, 1);
      wgmma_commit();
      wgmma_wait<GB>();
      mma_half<N>(d1, ca_lo + ca_half, ca_hi, ca_k2, cb_lo, b, k, 1);
      wgmma_commit();
      if (k == 0) mbar_arrive_cluster_if(crel, g.rel_lane);
      if (k == 2) prepare(kb + 1);
    }
  }
  if constexpr (OUTK) {
    GWAIT(g.bars + (B_GFULL + s) * 8, (g.phases >> s) & 1);
    const uint32_t a0 = a_lo, b0 = b_lo;
    wgmma_fence();
#pragma unroll
    for (int k = 0; k < 4; k++) {
      wgmma_wait<GD>();
      mma_half<N>(d0, a0, a_hi, a_k2, b0, b, k, 1);
      wgmma_commit();
      if (k == 1) prepare(NKB - 1);
    }
    GWAIT(g.bars + (B_GFULL + s) * 8, (g.phases >> s) & 1);
    wgmma_fence();
#pragma unroll
    for (int k = 0; k < 4; k++) {
      wgmma_wait<GD>();
      mma_half<N>(d0, a_lo, a_hi, a_k2, b_lo, b, k, 1);
      wgmma_commit();
    }
#pragma unroll
    for (int k = 0; k < 4; k++) mma_half<N>(d1, a0 + a_half, a_hi, a_k2, b0, b, k, 1);
#pragma unroll
    for (int k = 0; k < 4; k++) mma_half<N>(d1, a_lo + a_half, a_hi, a_k2, b_lo, b, k, 1);
    wgmma_commit();
  } else {
    GWAIT(g.bars + (B_GFULL + s) * 8, (g.phases >> s) & 1);
    g.phases ^= 1u << s;
    g.s = s;
    wgmma_fence();
#pragma unroll
    for (int k = 0; k < 4; k++) {
      wgmma_wait<GD>();
      mma_half<N>(d0, a_lo, a_hi, a_k2, b_lo, b, k, 1);
      wgmma_commit();
      if (RELX && k == GD) mbar_arrive_cluster_if(rel, g.rel_lane);
    }
#pragma unroll
    for (int k = 0; k < 4; k++) mma_half<N>(d1, a_lo + a_half, a_hi, a_k2, b_lo, b, k, 1);
    wgmma_commit();
  }
  wgmma_wait<1>();
  fence_regs(d0);
}
__device__ __forceinline__ void tile_drain(float (&d1)[96], GemmState& g) {
  wgmma_wait<0>();
  fence_regs(d1);
  mbar_arrive_cluster_if(g.rel_addr + g.s * 8, g.rel_lane);
}

__device__ __forceinline__ void tile_first(float (&d0)[96], float (&d1)[96], uint32_t sb, uint32_t rank, GemmState& g,
                                           const BFmt b) {
  float cs[6] = {0.f, 0.f, 0.f, 0.f, 0.f, 0.f};
  const int lane = threadIdx.x & 31, w = (threadIdx.x >> 5) & 3;
  const uint32_t a_c = g.lo0 + (1u << 16), b_c = g.lo0 + (16384 >> 4) + ((b.lbo >> 4) << 16);
  bool ready = false;
  uint32_t prev = 0;
  auto publish = [&]() {
    const uint32_t cs_dst = mapa(sb + kCsOff + rank * 768 + (8 * w + (lane >> 2)) * 4, lane & 1), cs_bar = mapa(g.bars + B_STAT * 8, lane & 1);
#pragma unroll
    for (int i = 0; i < 6; i++) cs[i] += __shfl_xor_sync(~0u, cs[i], 1);
#pragma unroll
    for (int i = 0; i < 6; i++) cs[i] += __shfl_xor_sync(~0u, cs[i], 2);
    if ((lane & 3) < 2) {
#pragma unroll
      for (int i = 0; i < 6; i++)
        asm volatile("st.async.weak.shared::cluster.mbarrier::complete_tx::bytes.b32 [%0], %1, [%2];\n" ::"r"(cs_dst + i * 128),
                     "r"(__float_as_uint(cs[i])), "r"(cs_bar)
                     : "memory");
    }
  };
  const uint32_t cs_base = sb + 16384 + rank * 12288 + lane * 64 + ((w ^ ((lane >> 1) & 3)) << 4);
  auto colsum = [&](uint32_t s) {
#pragma unroll
    for (int h = 0; h < 2; h++) {
      uint32_t bq[3][4];
#pragma unroll
      for (int i = 0; i < 3; i++)
        asm volatile("ldmatrix.sync.aligned.m8n8.x4.trans.shared.b16 {%0, %1, %2, %3}, [%4];\n"
                     : "=r"(bq[i][0]), "=r"(bq[i][1]), "=r"(bq[i][2]), "=r"(bq[i][3])
                     : "r"(cs_base + s * kSlot + (3 * h + i) * 2048)
                     : "memory");
#pragma unroll
      for (int i = 0; i < 3; i++)
        cs[3 * h + i] += ((bf_lo(bq[i][0]) + bf_hi(bq[i][0])) + (bf_lo(bq[i][1]) + bf_hi(bq[i][1]))) +
                         ((bf_lo(bq[i][2]) + bf_hi(bq[i][2])) + (bf_lo(bq[i][3]) + bf_hi(bq[i][3])));
    }
    asm volatile("" : "+f"(cs[0]), "+f"(cs[1]), "+f"(cs[2]), "+f"(cs[3]), "+f"(cs[4]), "+f"(cs[5])::"memory");
  };
  auto issue = [&](uint32_t s, int acc) {
    const uint32_t a_lo = a_c + s * (kSlot >> 4), b_lo = b_c + s * (kSlot >> 4);
    wgmma_fence();
#pragma unroll
    for (int k = 0; k < 4; k++) mma_half<192>(d0, a_lo, desc_hi(1024, 1), 64 >> 4, b_lo, b, k, (k > 0) ? 1 : acc);
    wgmma_commit();
#pragma unroll
    for (int k = 0; k < 4; k++) mma_half<192>(d1, a_lo + (8192 >> 4), desc_hi(1024, 1), 64 >> 4, b_lo, b, k, (k > 0) ? 1 : acc);
    wgmma_commit();
    wgmma_wait<2>();
    mbar_arrive_cluster_if(g.rel_addr + prev * 8, g.rel_lane && acc);
    prev = s;
  };
#pragma unroll 1
  for (int kb = 0; kb < 15; kb++) {
    const uint32_t s = (kb & 3) ^ ((kb >> 1) & 1);
    GWAIT(g.bars + (B_GFULL + s) * 8, (kb >> 2) & 1);
    issue(s, kb > 0);
    colsum(s);
    ready = mbar_test(g.bars + (B_GFULL + (((kb + 1) & 3) ^ (((kb + 1) >> 1) & 1))) * 8, ((kb + 1) >> 2) & 1);
  }
  GWAIT(g.bars + (B_GFULL + 2) * 8, 1);
  colsum(2);
  publish();
  issue(2, 1);
  g.s = 2;
}

__device__ __forceinline__ void epi_publish(uint32_t bar, int lane) {
  fence_async_smem();
  __syncwarp();
  if (lane == 0) mbar_arrive(bar);
}
constexpr float kQScale = 0.17677669529663687f * 1.4426950408889634f;
template <bool QKV>
__device__ __forceinline__ void epi192(const float (&d)[96], uint32_t base, const uint32_t (&off)[4]) {
#pragma unroll
  for (int jj = 0; jj < 12; jj++) {
    uint32_t r[4];
#pragma unroll
    for (int i = 0; i < 4; i++) {
      const float lo = d[8 * jj + 2 * i], hi = d[8 * jj + 2 * i + 1];
      r[i] = !QKV ? pack_bf16_relu(lo, hi) : (jj < 4 ? pack_bf16(lo * kQScale, hi * kQScale) : pack_bf16(lo, hi));
    }
    stsm4(base + (jj >> 2) * 16384 + off[jj & 3], r[0], r[1], r[2], r[3]);
  }
}
template <int CH, bool OUT>
__device__ __forceinline__ void epi128(const float (&d)[96], uint32_t base, const uint32_t (&off)[4]) {
  uint32_t x[4][4];
  if (OUT) {
#pragma unroll
    for (int q = 0; q < 4; q++) ldsm4(base + off[q], x[q][0], x[q][1], x[q][2], x[q][3]);
  }
#pragma unroll
  for (int q = 0; q < 4; q++) {
    uint32_t r[4];
#pragma unroll
    for (int i = 0; i < 4; i++) {
      const float lo = d[32 * CH + 8 * q + 2 * i], hi = d[32 * CH + 8 * q + 2 * i + 1];
      r[i] = OUT ? pack_bf16(lo + bf_lo(x[q][i]), hi + bf_hi(x[q][i])) : pack_bf16_relu(lo, hi);
    }
    stsm4(base + off[q], r[0], r[1], r[2], r[3]);
  }
}
__host__ __device__ constexpr uint32_t t0_chunk(int ch) {
  return ch == 0 ? 40960 : (ch == 1 ? 16384 : (ch == 2 ? 0 : (ch == 3 ? 24576 : (ch == 4 ? 8192 : 32768))));
}
template <int R>
__device__ __forceinline__ void epi_qkv_ln(const float (&d)[96], uint32_t cs_addr, uint32_t stat_addr, uint32_t base,
                                           uint32_t sw, uint32_t scol) {
  float m0, r0, m1, r1, c[4];
  asm volatile("ld.shared.v2.f32 {%0, %1}, [%2];\n" : "=f"(m0), "=f"(r0) : "r"(stat_addr));
  asm volatile("ld.shared.v2.f32 {%0, %1}, [%2];\n" : "=f"(m1), "=f"(r1) : "r"(stat_addr + 64));
  asm volatile("ld.shared.v2.f32 {%0, %1}, [%2];\n" : "=f"(c[0]), "=f"(c[1]) : "r"(cs_addr + R * 128));
  asm volatile("ld.shared.v2.f32 {%0, %1}, [%2];\n" : "=f"(c[2]), "=f"(c[3]) : "r"(cs_addr + R * 128 + 32));
#pragma unroll
  for (int q = 0; q < 6; q++) {
    const int jj = (q >> 1) * 4 + 2 * R + (q & 1), jn = ((q + 1) >> 1) * 4 + 2 * R + ((q + 1) & 1);
    const float f0 = jj < 4 ? kQScale * r0 : r0, f1 = jj < 4 ? kQScale * r1 : r1;
    uint32_t p[4];
#pragma unroll
    for (int i = 0; i < 2; i++) {
      p[2 * i] = pack_bf16(fmaf(-m0, c[2 * i], d[8 * jj + 4 * i]) * f0, fmaf(-m0, c[2 * i + 1], d[8 * jj + 4 * i + 1]) * f0);
      p[2 * i + 1] = pack_bf16(fmaf(-m1, c[2 * i], d[8 * jj + 4 * i + 2]) * f1, fmaf(-m1, c[2 * i + 1], d[8 * jj + 4 * i + 3]) * f1);
      if (q < 5) asm volatile("ld.shared.v2.f32 {%0, %1}, [%2];\n" : "=f"(c[2 * i]), "=f"(c[2 * i + 1]) : "r"(cs_addr + jn * 64 + 32 * i));
    }
    stsm4(base + t0_chunk(jj >> 1) + ((((jj & 1) * 2 + scol) ^ sw) << 4), p[0], p[1], p[2], p[3]);
  }
}

__device__ __noinline__ void attn_exact(float* o_out, uint32_t q_smem_row_addr, const uint8_t* kv_head) {
  const int lane = threadIdx.x & 31, g = lane >> 2, t = lane & 3;
  uint32_t qa[2][4];
  {
    const int r = (lane & 7) + ((lane >> 3) & 1) * 8;
#pragma unroll
    for (int k = 0; k < 2; k++) {
      const int c16 = 2 * k + (lane >> 4);
      ldsm4(q_smem_row_addr + r * 64 + ((c16 ^ ((r >> 1) & 3)) << 4), qa[k][0], qa[k][1], qa[k][2], qa[k][3]);
    }
  }
  float o[16];
#pragma unroll
  for (int i = 0; i < 16; i++) o[i] = 0.f;
  float m0 = -INFINITY, m1 = -INFINITY, l0 = 0.f, l1 = 0.f;
#pragma unroll 1
  for (int kc = 0; kc < kS / 16; kc++) {
    const uint8_t* kt = kv_head + (kc >> 2) * 8192;
    const int k0 = (kc & 3) * 16;
    float s[2][4];
#pragma unroll
    for (int nb = 0; nb < 2; nb++) {
      s[nb][0] = s[nb][1] = s[nb][2] = s[nb][3] = 0.f;
      const int key = k0 + nb * 8 + g;
#pragma unroll
      for (int k = 0; k < 2; k++) {
        const uint32_t b0 = __ldcg((const uint32_t*)(kt + key * 64 + (((2 * k) ^ ((key >> 1) & 3)) << 4) + t * 4));
        const uint32_t b1 = __ldcg((const uint32_t*)(kt + key * 64 + (((2 * k + 1) ^ ((key >> 1) & 3)) << 4) + t * 4));
        asm volatile(
            "mma.sync.aligned.m16n8k16.row.col.f32.bf16.bf16.f32 {%0,%1,%2,%3}, {%4,%5,%6,%7}, {%8,%9}, {%0,%1,%2,%3};\n"
            : "+f"(s[nb][0]), "+f"(s[nb][1]), "+f"(s[nb][2]), "+f"(s[nb][3])
            : "r"(qa[k][0]), "r"(qa[k][1]), "r"(qa[k][2]), "r"(qa[k][3]), "r"(b0), "r"(b1));
      }
    }
    float x0 = fmaxf(fmaxf(s[0][0], s[0][1]), fmaxf(s[1][0], s[1][1]));
    float x1 = fmaxf(fmaxf(s[0][2], s[0][3]), fmaxf(s[1][2], s[1][3]));
    x0 = fmaxf(x0, __shfl_xor_sync(~0u, x0, 1)); x1 = fmaxf(x1, __shfl_xor_sync(~0u, x1, 1));
    x0 = fmaxf(x0, __shfl_xor_sync(~0u, x0, 2)); x1 = fmaxf(x1, __shfl_xor_sync(~0u, x1, 2));
    x0 = fmaxf(x0, m0); x1 = fmaxf(x1, m1);
    const float c0 = ex2(m0 - x0), c1 = ex2(m1 - x1);
    m0 = x0; m1 = x1;
    uint32_t p[4];
    {
      const float e00 = ex2(s[0][0] - m0), e01 = ex2(s[0][1] - m0), e02 = ex2(s[0][2] - m1), e03 = ex2(s[0][3] - m1);
      const float e10 = ex2(s[1][0] - m0), e11 = ex2(s[1][1] - m0), e12 = ex2(s[1][2] - m1), e13 = ex2(s[1][3] - m1);
      l0 = l0 * c0 + (e00 + e01 + e10 + e11);
      l1 = l1 * c1 + (e02 + e03 + e12 + e13);
      p[0] = pack_bf16(e00, e01); p[1] = pack_bf16(e02, e03); p[2] = pack_bf16(e10, e11); p[3] = pack_bf16(e12, e13);
    }
    const uint8_t* vt = kt + 4096;
#pragma unroll
    for (int nb = 0; nb < 4; nb++) {
      uint32_t hv[4];
#pragma unroll
      for (int i = 0; i < 4; i++) {
        const int key = k0 + 2 * t + (i & 1) + (i >> 1) * 8;
        hv[i] = __ldcg((const unsigned short*)(vt + key * 64 + ((nb ^ ((key >> 1) & 3)) << 4) + g * 2));
      }
      const uint32_t b0 = hv[0] | (hv[1] << 16), b1 = hv[2] | (hv[3] << 16);
      o[4 * nb] *= c0; o[4 * nb + 1] *= c0; o[4 * nb + 2] *= c1; o[4 * nb + 3] *= c1;
      asm volatile(
          "mma.sync.aligned.m16n8k16.row.col.f32.bf16.bf16.f32 {%0,%1,%2,%3}, {%4,%5,%6,%7}, {%8,%9}, {%0,%1,%2,%3};\n"
          : "+f"(o[4 * nb]), "+f"(o[4 * nb + 1]), "+f"(o[4 * nb + 2]), "+f"(o[4 * nb + 3])
          : "r"(p[0]), "r"(p[1]), "r"(p[2]), "r"(p[3]), "r"(b0), "r"(b1));
    }
  }
  l0 += __shfl_xor_sync(~0u, l0, 1); l1 += __shfl_xor_sync(~0u, l1, 1);
  l0 += __shfl_xor_sync(~0u, l0, 2); l1 += __shfl_xor_sync(~0u, l1, 2);
  const float i0 = 1.f / l0, i1 = 1.f / l1;
#pragma unroll
  for (int nb = 0; nb < 4; nb++) {
    o_out[4 * nb] = o[4 * nb] * i0; o_out[4 * nb + 1] = o[4 * nb + 1] * i0;
    o_out[4 * nb + 2] = o[4 * nb + 2] * i1; o_out[4 * nb + 3] = o[4 * nb + 3] * i1;
  }
}

struct Params {
  CUtensorMap wqkv, w1a, w1b, w2, wo, x, out;
  const __nv_bfloat16* xptr;
  uint8_t* xn;
};

__global__ void __cluster_dims__(2, 1, 1) __launch_bounds__(kThreads, 1) fused_block_kernel(const __grid_constant__ Params P) {
  extern __shared__ __align__(1024) uint8_t smem_raw[];
  const uint32_t sb = (smem_u32(smem_raw) + 1023) & ~1023u;
  const uint32_t bars = sb + kBarOff;
  const int warp = __shfl_sync(~0u, threadIdx.x >> 5, 0);
  const int lane = threadIdx.x & 31;
  const uint32_t rank = blockIdx.x & 1;
  const int cl = blockIdx.x >> 1;
  const int c = ((cl & 1) << 2) | ((cl >> 3) & 3);
  const int m = (((cl & 6) | (cl >> 5)) << 1) + rank;

  if (warp == 0) {
    if (elect_one()) {
#pragma unroll
      for (int s = 0; s < 4; s++) mbar_init(bars + (B_GFULL + s) * 8, 1);
      mbar_init(bars + B_LN * 8, 1);
      fence_async_smem();
      mbar_expect_tx(bars + B_GFULL * 8, 16384 + 24576);
      tma_4d(sb + 16384, &P.wqkv, 32 * c, 0, 0, 0, bars + B_GFULL * 8);
      tma_4d(sb + 16384 + 12288, &P.wqkv, 32 * c, 32, 0, 0, bars + B_GFULL * 8);
      tma_2d(sb, &P.x, 0, 128 * m, bars + B_GFULL * 8);
    }
  } else if (elect_one()) {
    const uint32_t cc = (uint32_t)(0x55455500FFC00AAull >> (4 * (warp - 1)));
    mbar_init(bars + (2 * warp + 2) * 8, (cc & 3) ? (2u << (cc & 3)) : 1u);
    mbar_init(bars + (2 * warp + 3) * 8, (cc & 12) ? (2u << ((cc >> 2) & 3)) : 1u);
  }
  asm volatile("fence.mbarrier_init.release.cluster;\n" ::: "memory");
  if (threadIdx.x >= 256) {
    asm volatile("st.shared.b32 [%0], %1;\n" ::"r"(sb + kOnesOff + (threadIdx.x - 256) * 4), "r"(0x3f803f80u) : "memory");
    fence_async_smem();
  }
  __syncthreads();
  cluster_arrive();

  if (warp < 4) {
    asm volatile("setmaxnreg.dec.sync.aligned.u32 32;\n");
    if (warp == 0) {
      cluster_wait();
      if (elect_one()) {
#pragma unroll
        for (int kb = 1; kb < 4; kb++) {
          const int s = kb ^ (kb >> 1);
          mbar_expect_tx(bars + (B_GFULL + s) * 8, 16384 + 24576);
          tma_4d_mc(sb + s * kSlot + 16384 + rank * 12288, &P.wqkv, 32 * c, kb * 64 + rank * 32, 0, 0, bars + (B_GFULL + s) * 8);
          tma_2d(sb + s * kSlot, &P.x, kb * 64, 128 * m, bars + (B_GFULL + s) * 8);
        }
        mbar_expect_tx(bars + B_LN * 8, 32768);
        bulk_g2s(sb + kKvOff, P.xptr + (size_t)(m * 128 + c * 16) * kD, 32768, bars + B_LN * 8);
      }
    }
    if (warp == 1 && lane == 0) { prefetch_map(&P.w1a); prefetch_map(&P.w1b); prefetch_map(&P.w2); prefetch_map(&P.wo); }
    if (warp == 2 && lane == 0) prefetch_map(&P.out);
    __syncwarp();
    if (warp != 0) cluster_wait();
    unsigned ep;
    asm volatile("ld.relaxed.gpu.global.u32 %0, [%1];\n" : "=r"(ep) : "l"(&g_flags[F_EPOCH * 32]) : "memory");
    ep = __shfl_sync(~0u, ep, 0) + 1;
    const bool lead = elect_one();
    {
      if (warp == 0) {
        uint32_t ph = 0, r3 = 0;
        uint32_t full, dst;
        auto acquire = [&](int pos, bool early, uint32_t bytes) {
          const uint32_t s = next_slot(pos, early, r3);
          full = bars + s * 8;
          dst = sb + s * kSlot;
          const uint32_t par = (ph >> s) & 1;
          ph ^= 1u << s;
          mbar_wait(full + B_GEMPTY * 8, par);
          if (lead) mbar_expect_tx(full, bytes);
        };
        const int kr = rank * 32;
#pragma unroll 1
        for (int kb = 4; kb < 16; kb++) {
          acquire(kb, true, 16384 + 24576);
          if (lead) tma_4d_mc(dst + 16384 + rank * 12288, &P.wqkv, 32 * c, kb * 64 + kr, 0, 0, full);
          if (lead) tma_2d(dst, &P.x, kb * 64, 128 * m, full);
        }
        const uint8_t* xn = P.xn + (size_t)m * 16 * 16384;
#pragma unroll 1
        for (int kb = 0; kb < 16; kb++) {
          acquire(kb, true, 16384 + 24576);
          if (lead) tma_4d_mc(dst + 16384 + rank * 12288, &P.wqkv, 32 * c, kb * 64 + kr, 2, 0, full);
          if (kb == 0) { flag_wait(&g_flags[(F_XN + m) * 32], 64 * ep); }
          if (lead) bulk_g2s(dst, xn + kb * 16384, 16384, full);
        }
#pragma unroll 1
        for (int kb = 0; kb < 16; kb++) {
          acquire(kb, false, 16384 + 24576);
          if (lead) bulk_g2s(dst, xn + kb * 16384, 16384, full);
          if (lead) tma_3d_mc(dst + 16384 + rank * 12288, &P.w1a, 0, kb * 64 + kr, 7 * c, full);
        }
#pragma unroll 1
        for (int i = 0; i < 32; i++) {
          const int kb = i & 15;
          acquire(kb, i >= 16, 32768);
          if (lead) bulk_g2s(dst, xn + kb * 16384, 16384, full);
          if (lead) tma_3d_mc(dst + 16384 + rank * 8192, &P.w1b, 0, kb * 64 + kr, 7 * c + 3 + (i >> 4) * 2, full);
        }
        const uint8_t* hb = g_h + (size_t)m * 56 * 16384;
        const uint8_t* ob = g_o + (size_t)m * 32 * 8192;
        int pos = 0;
        auto out_h = [&](int n, int hk, int run, int skip, const unsigned* flag) {
          int cnt = 0;
#pragma unroll 1
          for (int i = 0; i < n; i++, pos++) {
            acquire(pos, true, 32768);
            if (lead) tma_3d_mc(dst + 16384 + rank * 8192, &P.w2, 0, hk * 64 + kr, 2 * c, full);
            if (i == 0) flag_wait(flag, 16 * ep);
            if (lead) bulk_g2s(dst, hb + hk * 16384, 16384, full);
            hk++;
            if (++cnt == run) { cnt = 0; hk += skip; }
          }
        };
        auto out_o = [&](int j0, int j1) {
#pragma unroll 1
          for (int j = j0; j < j1; j++, pos++) {
            acquire(pos, true, 32768);
            if (lead) tma_3d_mc(dst + 16384 + rank * 8192, &P.wo, 0, j * 64 + kr, 2 * c, full);
            if ((j & 3) == 0) flag_wait(&g_flags[(F_O + m * 4 + (j >> 2)) * 32], 16 * ep);
            if (lead) bulk_g2s(dst, ob + j * 16384, 16384, full);
          }
        };
        out_h(24, 0, 3, 4, &g_flags[(F_H + m * 3 + 0) * 32]);
        out_h(16, 3, 2, 5, &g_flags[(F_H + m * 3 + 1) * 32]);
        out_o(0, 8);
        out_h(16, 5, 2, 5, &g_flags[(F_H + m * 3 + 2) * 32]);
        if (lead) { tma_pf_2d(&P.x, 128 * c, 128 * m); tma_pf_2d(&P.x, 128 * c + 64, 128 * m); }
        out_o(8, 16);
        if (lead) {
          mbar_expect_tx(bars + B_STAT * 8, 32768);
          tma_2d(sb + kKvOff, &P.x, 128 * c, 128 * m, bars + B_STAT * 8);
          tma_2d(sb + kKvOff + 16384, &P.x, 128 * c + 64, 128 * m, bars + B_STAT * 8);
        }
      } else if (warp == 1) {
        flag_wait(&g_flags[(F_XN + m) * 32], 64 * ep);
        if (lead) mbar_expect_tx(bars + B_STAT * 8, 1024 + 1536);
        if (lead) bulk_g2s(sb + kQOff + 8192, g_stat + m * 128, 1024, bars + B_STAT * 8);
        uint32_t ph = 1, full = bars + B_KVFULL * 8, dst = sb + kKvOff + rank * 4096;
        const uint8_t* src = g_kv + (size_t)c * 32 * 8192 + rank * 4096;
#pragma unroll 1
        for (int g = 0; g <= 128; g++) {
          if ((g & 31) == 0 && g < 128) {
            const int u = g >> 5, head = 8 * u + c;
            flag_wait(&g_flags[(F_KV + head) * 32], 32 * ep);
            if (u >= 2) mbar_wait(bars + (B_QEMPTY + (u & 1)) * 8, 0);
            if (u && lead) mbar_expect_tx(bars + (B_QFULL + (u & 1)) * 8, 8192);
            if (u && lead) bulk_g2s(sb + kQOff + (u & 1) * 8192, g_o + ((size_t)m * 32 + head) * 8192, 8192, bars + (B_QFULL + (u & 1)) * 8);
          }
          if (g == 2) flag_wait(&g_flags[(F_KV + 8 + c) * 32], 32 * ep);
          mbar_wait(full + (B_KVEMPTY - B_KVFULL) * 8, ph);
          if (lead) mbar_expect_tx(full, 8192);
          if (lead) bulk_g2s_mc(dst, src, 4096, full);
          const int t = g + 1 - (int)rank;
          if (t > 0 && t < 128) src += (t & 31) ? 8192 : 8192 + 7 * 32 * 8192;
          full += 8;
          dst += 8192;
          if (full == bars + (B_KVFULL + kNKv) * 8) { full -= kNKv * 8; dst -= kNKv * 8192; ph ^= 1; }
        }
      } else if (lane != 0) {
      } else if (warp == 2) {
        const uint32_t st = sb + kStageOff;
        auto store_head = [&](uint32_t src, int head, int r, int h) {
          uint8_t* kv = g_kv + ((size_t)head * 32 + 2 * m + h) * 8192;
          bulk_s2g_paced(kv, src + (2 + r) * 8192 + h * 4096, 4096);
          bulk_s2g_paced(kv + 4096, src + (4 + r) * 8192 + h * 4096, 4096);
          bulk_s2g_paced(g_o + ((size_t)m * 32 + head) * 8192 + h * 4096, src + r * 8192 + h * 4096, 4096);
        };
        {
          const uint32_t s0 = sb + kKvOff;
          uint8_t* kv = g_kv + ((size_t)c * 32 + 2 * m) * 8192;
          mbar_wait(bars + B_GST0 * 8, 0);
          bulk_s2g(kv, s0 + t0_chunk(2), 4096);
          bulk_s2g(kv + 4096, s0 + t0_chunk(4), 4096);
          mbar_wait(bars + B_GST * 8, 0);
          bulk_s2g(kv + 8192, s0 + t0_chunk(2) + 4096, 4096);
          bulk_s2g(kv + 12288, s0 + t0_chunk(4) + 4096, 4096);
          bulk_commit();
          mbar_arrive(bars + B_QFULL * 8);
          bulk_wait_all();
          flag_add(&g_flags[(F_KV + c) * 32], 2);
          mbar_wait(bars + (B_GST + 1) * 8, 0);
          mbar_arrive_cta(bars + B_GST0 * 8, rank, 4);
          kv += (size_t)8 * 32 * 8192;
          bulk_s2g_paced(g_o + ((size_t)m * 32 + 8 + c) * 8192, s0 + t0_chunk(1), 8192);
#pragma unroll 1
          for (int h = 0; h < 2; h++) {
            bulk_s2g_paced(kv + h * 8192, s0 + t0_chunk(3) + h * 4096, 4096);
            bulk_s2g_paced(kv + h * 8192 + 4096, s0 + t0_chunk(5) + h * 4096, 4096);
          }
          bulk_wait_all();
          flag_add(&g_flags[(F_KV + 8 + c) * 32], 2);
        }
#pragma unroll 1
        for (int t = 1; t < 5; t++) {
#pragma unroll 1
          for (int h = 0; h < 2; h++) {
            mbar_wait(bars + (B_GST + h) * 8, t & 1);
            if (t < 2) {
              store_head(st, 16 + c, 0, h);
              store_head(st, 24 + c, 1, h);
            } else {
              const int a0 = t == 2 ? 7 * c : 7 * c + 2 * t - 3, na = t == 2 ? 3 : 2;
#pragma unroll 1
              for (int a = 0; a < na; a++)
                bulk_s2g_paced(g_h + ((size_t)m * 56 + a0 + a) * 16384 + h * 8192,
                               t == 2 ? st + a * 16384 + h * 8192 : sb + (2 * h + a) * kSlot + 32768, 8192);
            }
            bulk_commit();
          }
          bulk_wait_read();
          if (t < 3) {
            mbar_arrive_cta(bars + (B_GEMPTY + 3) * 8, 0, 4);
            mbar_arrive_cta(bars + (B_GEMPTY + 3) * 8, 1, 4);
          } else {
            mbar_arrive_cta(bars + B_GST0 * 8, rank, 4);
          }
          bulk_wait_all();
          if (t < 2) {
            flag_add(&g_flags[(F_KV + 16 * t + c) * 32], 2);
            flag_add(&g_flags[(F_KV + 16 * t + 8 + c) * 32], 2);
          } else {
            flag_add(&g_flags[(F_H + m * 3 + t - 2) * 32], 2);
          }
        }
#pragma unroll 1
        for (int i = 0; i < 4; i++) {
          mbar_wait(bars + (B_OUT + i) * 8, 0);
          tma_store_2d(&P.out, sb + kKvOff + (i & 1) * 16384 + (i >> 1) * 8192, 128 * c + 64 * (i & 1), 128 * m + 64 * (i >> 1));
          bulk_commit();
        }
        bulk_wait_read();
      } else {
#pragma unroll 1
        for (int u = 0; u < 4; u++) {
          for (int w = 0; w < 2; w++) {
            mbar_wait(bars + (B_AST + w * 2 + (u & 1)) * 8, u >> 1);
            bulk_s2g(g_o + ((size_t)m * 32 + 8 * u + c) * 8192 + w * 4096, sb + kQOff + (u & 1) * 8192 + w * 4096, 4096);
            bulk_commit();
          }
          bulk_wait_read();
          mbar_arrive(bars + (B_QEMPTY + (u & 1)) * 8);
          bulk_wait_all();
          flag_add(&g_flags[(F_O + m * 4 + u) * 32], 2);
        }
      }
    }
    __syncwarp();
  } else if (warp < 8) {
    asm volatile("setmaxnreg.inc.sync.aligned.u32 240;\n");
    cluster_wait();
    const int w = warp & 3;
    GemmState g;
    g.lo0 = (sb & 0x3FFFF) >> 4;
    asm volatile("" : "+r"(g.lo0));
    g.lo0 = __shfl_sync(~0u, g.lo0, 0);
    g.bars = bars;
    g.rel_addr = mapa(bars + B_GEMPTY * 8, lane & 1);
    g.rel_lane = lane < 2;
    g.zero = blockIdx.x >> 16;
    g.phases = 0; g.r3 = 0; g.s = 0;
    const BFmt fq = {2048, desc_hi(512, 2), 1024 >> 4, 12288 >> 4};
    const BFmt f192 = {4096, desc_hi(1024, 1), 2048 >> 4, 12288 >> 4};
    const BFmt f128 = {4096, desc_hi(1024, 1), 2048 >> 4, 8192 >> 4};
    const uint32_t srow = w * 16 + (lane & 7) + ((lane >> 3) & 1) * 8, scol = lane >> 4;
    const uint32_t st = sb + kStageOff;
    const uint32_t gst0 = bars + B_GST * 8, gst1 = gst0 + 8;
    const uint32_t sw64 = (srow >> 1) & 3, b128 = srow * 128, sw128 = srow & 7;
    float d0[96], d1[96];
    tile_first(d0, d1, sb, rank, g, fq);
    const uint32_t csb = sb + kCsOff;
    mbar_wait(bars + B_STAT * 8, 0);
    if (threadIdx.x < 128 + 96) {
      const uint32_t a = csb + (threadIdx.x - 128) * 8;
      float x0, x1, y0, y1;
      asm volatile("ld.shared.v2.f32 {%0, %1}, [%2];\n" : "=f"(x0), "=f"(x1) : "r"(a));
      asm volatile("ld.shared.v2.f32 {%0, %1}, [%2];\n" : "=f"(y0), "=f"(y1) : "r"(a + 768));
      asm volatile("st.shared.v2.f32 [%0], {%1, %2};\n" ::"r"(a), "f"(x0 + y0), "f"(x1 + y1) : "memory");
    }
    const uint32_t stat = sb + kQOff + 8192 + (w * 16 + (lane >> 2)) * 8;
    wgmma_wait<1>();
    fence_regs(d0);
    named_sync(1);
    const uint32_t b0 = sb + kKvOff + srow * 64;
    epi_qkv_ln<0>(d0, csb + (lane & 3) * 8, stat, b0, sw64, scol);
    epi_publish(bars + B_GST0 * 8, lane);
    epi_qkv_ln<1>(d0, csb + (lane & 3) * 8, stat, b0, sw64, scol);
    tile_drain(d1, g);
    tile_head<192>(d0, g, fq);
    epi_qkv_ln<0>(d1, csb + (lane & 3) * 8, stat + 512, b0 + 4096, sw64, scol);
    epi_publish(gst0, lane);
    epi_qkv_ln<1>(d1, csb + (lane & 3) * 8, stat + 512, b0 + 4096, sw64, scol);
    epi_publish(gst1, lane);
    uint32_t off[4];
#pragma unroll
    for (int q = 0; q < 4; q++) off[q] = srow * 64 + (q >> 1) * 8192 + ((((q & 1) * 2 + scol) ^ sw64) << 4);
    tile_body<192, 16, kDepth192, false, true, false>(d0, d1, g, fq);
    mbar_wait(bars + B_GST0 * 8, 1);
    named_sync(1);
    epi192<true>(d0, st, off);
    epi_publish(gst0, lane);
    tile_drain(d1, g);
    tile_head<192>(d0, g, f192);
    epi192<true>(d1, st + 4096, off);
    epi_publish(gst1, lane);
#pragma unroll
    for (int q = 0; q < 4; q++) off[q] = b128 + (((q * 2 + scol) ^ sw128) << 4);
    tile_body<192, 16, kDepth192, false, false, false>(d0, d1, g, f192);
    named_sync(1);
    epi192<false>(d0, st, off);
    epi_publish(gst0, lane);
    tile_drain(d1, g);
    tile_head<128>(d0, g, f128);
    epi192<false>(d1, st + 8192, off);
    epi_publish(gst1, lane);
#pragma unroll
    for (int t = 3; t < 5; t++) {
      if (t == 3) tile_body<128, 16, kDepth128, false, false, true>(d0, d1, g, f128);
      else tile_body<128, 16, kDepth128, false, true, true>(d0, d1, g, f128);
      if (t == 4) mbar_wait(bars + B_GST0 * 8, 0);
      epi128<0, false>(d0, sb + 32768, off);
      epi128<1, false>(d0, sb + kSlot + 32768, off);
      epi_publish(gst0, lane);
      tile_drain(d1, g);
      tile_head<128>(d0, g, f128);
      epi128<0, false>(d1, sb + 2 * kSlot + 32768, off);
      epi128<1, false>(d1, sb + 3 * kSlot + 32768, off);
      epi_publish(gst1, lane);
    }
    tile_body<128, 72, kDepth128, true, true, false>(d0, d1, g, f128);
    mbar_wait(bars + B_STAT * 8, 1);
    epi128<0, true>(d0, sb + kKvOff, off);
    epi_publish(bars + (B_OUT + 0) * 8, lane);
    epi128<1, true>(d0, sb + kKvOff + 16384, off);
    epi_publish(bars + (B_OUT + 1) * 8, lane);
    wgmma_wait<0>();
    fence_regs(d1);
    epi128<0, true>(d1, sb + kKvOff + 8192, off);
    epi_publish(bars + (B_OUT + 2) * 8, lane);
    epi128<1, true>(d1, sb + kKvOff + 16384 + 8192, off);
    epi_publish(bars + (B_OUT + 3) * 8, lane);
  } else {
    asm volatile("setmaxnreg.dec.sync.aligned.u32 120;\n");
    {
      const int r0 = c * 16 + (warp - 8) * 2;
      const uint32_t lnbuf = sb + kKvOff + (warp - 8) * 4096;
      const uint32_t statbuf = sb + kKvOff + 32768 + (warp - 8) * 16;
      mbar_wait(bars + B_LN * 8, 0);
      uint4 v[2][4];
#pragma unroll
      for (int i = 0; i < 2; i++)
#pragma unroll
        for (int j = 0; j < 4; j++)
          asm volatile("ld.shared.v4.b32 {%0, %1, %2, %3}, [%4];\n"
                       : "=r"(v[i][j].x), "=r"(v[i][j].y), "=r"(v[i][j].z), "=r"(v[i][j].w)
                       : "r"(lnbuf + i * 2048 + (lane + 32 * j) * 16)
                       : "memory");
      __syncwarp();
#pragma unroll
      for (int i = 0; i < 2; i++) {
        float f[32];
#pragma unroll
        for (int j = 0; j < 4; j++) {
          f[8 * j] = bf_lo(v[i][j].x); f[8 * j + 1] = bf_hi(v[i][j].x); f[8 * j + 2] = bf_lo(v[i][j].y); f[8 * j + 3] = bf_hi(v[i][j].y);
          f[8 * j + 4] = bf_lo(v[i][j].z); f[8 * j + 5] = bf_hi(v[i][j].z); f[8 * j + 6] = bf_lo(v[i][j].w); f[8 * j + 7] = bf_hi(v[i][j].w);
        }
        float sum = 0.f, sq = 0.f;
#pragma unroll
        for (int j = 0; j < 32; j++) sum += f[j];
#pragma unroll
        for (int o = 16; o; o >>= 1) sum += __shfl_xor_sync(~0u, sum, o);
        const float mean = sum * (1.f / kD);
#pragma unroll
        for (int j = 0; j < 32; j++) { const float dlt = f[j] - mean; sq = fmaf(dlt, dlt, sq); }
#pragma unroll
        for (int o = 16; o; o >>= 1) sq += __shfl_xor_sync(~0u, sq, o);
        const float mb = bf_round(mean);
        const float den = bf_round(sqrtf(bf_round(bf_round(sq * (1.f / kD)) + 1e-5f)));
        const float inv = 1.f / den;
        const float ih = bf_round(inv);
        const uint32_t mb2 = pack_bf16(mb, mb), ih2 = pack_bf16(ih, ih), il2 = pack_bf16(inv - ih, inv - ih);
        const int r = r0 + i;
        if (lane == 0) asm volatile("st.shared.v2.f32 [%0], {%1, %2};\n" ::"r"(statbuf + i * 8), "f"(mb), "f"(inv) : "memory");
#pragma unroll
        for (int j = 0; j < 4; j++) {
          uint4 o;
          uint32_t dd[4];
#pragma unroll
          for (int e = 0; e < 4; e++) {
            const uint32_t xr = e == 0 ? v[i][j].x : (e == 1 ? v[i][j].y : (e == 2 ? v[i][j].z : v[i][j].w));
            uint32_t t;
            asm("sub.rn.bf16x2 %0, %1, %2;" : "=r"(t) : "r"(xr), "r"(mb2));
            uint32_t lo;
            asm("mul.rn.bf16x2 %0, %1, %2;" : "=r"(lo) : "r"(t), "r"(il2));
            asm("fma.rn.bf16x2 %0, %1, %2, %3;" : "=r"(dd[e]) : "r"(t), "r"(ih2), "r"(lo));
          }
          o.x = dd[0]; o.y = dd[1]; o.z = dd[2]; o.w = dd[3];
          const int ch = lane + 32 * j;
          asm volatile("st.shared.v4.b32 [%0], {%1, %2, %3, %4};\n" ::"r"(lnbuf + (ch >> 3) * 256 + i * 128 + (((ch & 7) ^ (r & 7)) << 4)),
                       "r"(o.x), "r"(o.y), "r"(o.z), "r"(o.w)
                       : "memory");
        }
      }
      fence_async_smem();
      __syncwarp();
      if (lane < 17) {
        if (lane < 16) bulk_s2g(P.xn + ((size_t)(m * 16 + lane) * 128 + r0) * 128, lnbuf + lane * 256, 256);
        else bulk_s2g(g_stat + m * 128 + r0, statbuf, 16);
        bulk_commit();
        bulk_wait_all();
      }
      __syncwarp();
      if (lane == 0) flag_add(&g_flags[(F_XN + m) * 32], 1);
    }
    cluster_wait();
    const int aw = (warp - 8) >> 2, w = warp & 3;
    const bool rel_lane = lane < 2;
    const uint32_t rel_addr = mapa(bars + B_KVEMPTY * 8, lane & 1);
    float s[32], o[20];
    uint32_t pa[16], pb[16];
#pragma unroll
    for (int i = 0; i < 16; i++) { pa[i] = 0u; pb[i] = 0u; }
#pragma unroll
    for (int i = 0; i < 20; i++) o[i] = 0.f;
#pragma unroll
    for (int i = 0; i < 32; i++) s[i] = 0.f;
    const uint32_t hi64 = desc_hi(512, 2);
    const uint32_t kv_lo0 = desc_lo(sb + kKvOff, 16);
    uint32_t st = 0, ph = 0, q_lo = 0;
    uint32_t rel_prev = rel_addr;
    bool ready = false, pend = false;
    const uint32_t v_lo0 = desc_lo(sb + kKvOff + 4096, kOnesOff - kKvOff - 4096);
    auto issue_pv = [&](uint32_t (&p)[16], int acc) {
      const uint32_t v_lo = v_lo0 + st * (512u - (512u << 16));
      wgmma_rs_n40<1>(o, p[0], p[1], p[2], p[3], mk_desc(v_lo, hi64), acc);
      wgmma_rs_n40<1>(o, p[4], p[5], p[6], p[7], mk_desc(v_lo + (64u - (64u << 16)), hi64), 1);
      wgmma_rs_n40<1>(o, p[8], p[9], p[10], p[11], mk_desc(v_lo + (128u - (128u << 16)), hi64), 1);
      wgmma_rs_n40<1>(o, p[12], p[13], p[14], p[15], mk_desc(v_lo + (192u - (192u << 16)), hi64), 1);
    };
    auto issue_qk = [&]() {
      const uint32_t k_lo = kv_lo0 + st * 512;
      wgmma_ss_n64<0>(s, mk_desc(q_lo, hi64), mk_desc(k_lo, hi64), 0);
      wgmma_ss_n64<0>(s, mk_desc(q_lo + 2, hi64), mk_desc(k_lo + 2, hi64), 1);
    };
    auto softmax_tile = [&](uint32_t (&p)[16]) {
#pragma unroll
      for (int i = 0; i < 8; i++) {
        const float e0 = ex2(s[4 * i]), e1 = ex2(s[4 * i + 1]), e2 = ex2(s[4 * i + 2]), e3 = ex2(s[4 * i + 3]);
        p[2 * i] = pack_bf16(e0, e1); p[2 * i + 1] = pack_bf16(e2, e3);
      }
    };
    auto advance = [&]() {
      rel_prev = rel_addr + st * 8;
      if (++st == kNKv) { st = 0; ph ^= 1; }
      ready = mbar_test(bars + (B_KVFULL + st) * 8, ph);
    };
    uint32_t r[8];
    auto finish = [&](int u) {
      const uint32_t ob = sb + kQOff + (u & 1) * 8192 + aw * 4096;
      const float t0 = o[16], t1 = o[18];
      float z[4] = {0.f, 0.f, 0.f, 0.f};
#pragma unroll
      for (int i = 0; i < 16; i++) asm("fma.rn.f32 %0, %1, 0f00000000, %0;" : "+f"(z[i & 3]) : "f"(o[i]));
      const bool ok = (fminf(t0, t1) >= 8.271806e-25f) & (fmaxf(t0, t1) <= 1.2676506e30f) & (((z[0] + z[1]) + (z[2] + z[3]) + t0 * 0.f + t1 * 0.f) == 0.f);
      float i0, i1;
      asm("rcp.approx.ftz.f32 %0, %1;" : "=f"(i0) : "f"(t0));
      asm("rcp.approx.ftz.f32 %0, %1;" : "=f"(i1) : "f"(t1));
#pragma unroll
      for (int i = 0; i < 4; i++) {
        r[2 * i] = pack_bf16(o[4 * i] * i0, o[4 * i + 1] * i0);
        r[2 * i + 1] = pack_bf16(o[4 * i + 2] * i1, o[4 * i + 3] * i1);
      }
      if (__any_sync(~0u, !ok)) {
        float e[16];
        attn_exact(e, ob + w * 1024, g_kv + (size_t)(8 * u + c) * 32 * 8192);
#pragma unroll
        for (int i = 0; i < 8; i++) r[i] = pack_bf16(e[2 * i], e[2 * i + 1]);
      }
      __syncwarp();
    };
    auto publish_o = [&](int u) {
      const uint32_t srow = w * 16 + (lane & 7) + ((lane >> 3) & 1) * 8, scol = lane >> 4;
      const uint32_t base = sb + kQOff + (u & 1) * 8192 + aw * 4096 + srow * 64, sw = (srow >> 1) & 3;
      stsm4(base + ((scol ^ sw) << 4), r[0], r[1], r[2], r[3]);
      stsm4(base + (((2 + scol) ^ sw) << 4), r[4], r[5], r[6], r[7]);
      epi_publish(bars + (B_AST + aw * 2 + (u & 1)) * 8, lane);
    };
    auto issue = [&](uint32_t (&pin)[16], uint32_t (&pout)[16], int acc, int pub) {
      fence_regs(s); fence_regs(o); fence_regs(pin); fence_regs(pout);
      wgmma_fence();
      issue_qk();
      wgmma_commit();
      issue_pv(pin, acc);
      wgmma_commit();
      mbar_arrive_cluster_if(rel_prev, rel_lane && pend);
      pend = true;
      if (pub >= 0) publish_o(pub);
      wgmma_wait<1>();
      fence_regs(s);
      advance();
    };
    mbar_wait(bars + B_KVFULL * 8, 0);
#pragma unroll 1
    for (int it = 0; it <= 64; it++) {
      const bool bnd = (it & 15) == 0;
      const int u = it >> 4;
      if (bnd) {
        q_lo = desc_lo(sb + kQOff + (u & 1) * 8192 + aw * 4096, 16);
        if (u < 4) mbar_wait(bars + (B_QFULL + (u & 1)) * 8, u >> 1);
      }
      issue(pb, pa, 1, -1);
      if (it < 64) {
        softmax_tile(pa);
        if (!ready) mbar_wait(bars + (B_KVFULL + st) * 8, ph);
      }
      wgmma_wait<0>();
      if (bnd) {
        fence_regs(o);
        if (it > 0) finish(u - 1);
        if (it == 64) { publish_o(3); break; }
      }
      issue(pa, pb, !bnd, bnd ? u - 1 : -1);
      softmax_tile(pb);
      if (!ready) mbar_wait(bars + (B_KVFULL + st) * 8, ph);
      wgmma_wait<0>();
    }
  }

  cluster_arrive();
  cluster_wait();
  if (m == 0 && c == 0 && threadIdx.x == 0) flag_add(&g_flags[F_EPOCH * 32], 1);
}

typedef CUresult (*EncodeFn)(CUtensorMap*, CUtensorMapDataType, cuuint32_t, void*, const cuuint64_t*, const cuuint64_t*,
                             const cuuint32_t*, const cuuint32_t*, CUtensorMapInterleave, CUtensorMapSwizzle,
                             CUtensorMapL2promotion, CUtensorMapFloatOOBfill);

void encode(EncodeFn fn, CUtensorMap* map, const void* base, int rank, const cuuint64_t* dims, const cuuint64_t* strides,
            const cuuint32_t* box, CUtensorMapSwizzle sw) {
  const cuuint32_t es[5] = {1, 1, 1, 1, 1};
  fn(map, CU_TENSOR_MAP_DATA_TYPE_BFLOAT16, rank, const_cast<void*>(base), dims, strides, box, es,
     CU_TENSOR_MAP_INTERLEAVE_NONE, sw, CU_TENSOR_MAP_L2_PROMOTION_L2_128B, CU_TENSOR_MAP_FLOAT_OOB_FILL_NONE);
}

}

extern "C" void kernel_launch(void* const* d_in, const int* in_sizes, int n_in, void* d_out, int out_size) {
  (void)in_sizes; (void)n_in; (void)out_size;
  static Params P;
  static const void* key[6] = {nullptr, nullptr, nullptr, nullptr, nullptr, nullptr};
  const void* cur[6] = {d_in[0], d_in[1], d_in[2], d_in[4], d_in[5], d_out};
  bool same = true;
  for (int i = 0; i < 6; i++) same = same && key[i] == cur[i];
  if (!same) {
    void* fn = nullptr;
    cudaDriverEntryPointQueryResult q;
    cudaGetDriverEntryPoint("cuTensorMapEncodeTiled", &fn, cudaEnableDefault, &q);
    EncodeFn enc = (EncodeFn)fn;
    {
      const cuuint64_t d[4] = {256, 1024, 4, 3}, s[3] = {6144, 512, 2048};
      const cuuint32_t b[4] = {32, 32, 2, 3};
      encode(enc, &P.wqkv, d_in[1], 4, d, s, b, CU_TENSOR_MAP_SWIZZLE_64B);
    }
    {
      const cuuint64_t d[3] = {64, 1024, 56}, s[2] = {kDff * 2, 128};
      const cuuint32_t b3[3] = {64, 32, 3}, b2[3] = {64, 32, 2};
      encode(enc, &P.w1a, d_in[4], 3, d, s, b3, CU_TENSOR_MAP_SWIZZLE_128B);
      encode(enc, &P.w1b, d_in[4], 3, d, s, b2, CU_TENSOR_MAP_SWIZZLE_128B);
    }
    {
      const cuuint64_t d2[3] = {64, kDff, 16}, d1[3] = {64, kD, 16}, s[2] = {kD * 2, 128};
      const cuuint32_t b[3] = {64, 32, 2};
      encode(enc, &P.w2, d_in[5], 3, d2, s, b, CU_TENSOR_MAP_SWIZZLE_128B);
      encode(enc, &P.wo, d_in[2], 3, d1, s, b, CU_TENSOR_MAP_SWIZZLE_128B);
    }
    {
      const cuuint64_t d[2] = {kD, kS}, s[1] = {kD * 2};
      const cuuint32_t bx[2] = {64, 128}, bo[2] = {64, 64};
      encode(enc, &P.x, d_in[0], 2, d, s, bx, CU_TENSOR_MAP_SWIZZLE_128B);
      encode(enc, &P.out, d_out, 2, d, s, bo, CU_TENSOR_MAP_SWIZZLE_128B);
    }
    P.xptr = (const __nv_bfloat16*)d_in[0];
    P.xn = (uint8_t*)d_out;
    cudaFuncSetAttribute(fused_block_kernel, cudaFuncAttributeMaxDynamicSharedMemorySize, kSmemBytes);
    for (int i = 0; i < 6; i++) key[i] = cur[i];
  }
  fused_block_kernel<<<kCtas, kThreads, kSmemBytes>>>(P);
}
```
